```python
import torch

def _softmax(x, axis=-1):
    return torch.softmax(x, dim=axis)
def _gelu(x):
    return torch.nn.functional.gelu(x, approximate="tanh")
def _silu(x):
    return torch.nn.functional.silu(x)
def _sigmoid(x):
    return torch.sigmoid(x)
def _layernorm(x, axis=-1, eps=1e-5):
    m = x.mean(dim=axis, keepdim=True)
    v = x.var(dim=axis, keepdim=True, unbiased=False)
    return (x - m) / torch.sqrt(v + eps)
def _scatter_add(tgt, idx, src, axis=0):
    return tgt.clone().index_add_(axis, idx, src)
def _segment_sum(src, seg, n):
    out = torch.zeros((n,) + src.shape[1:], dtype=src.dtype)
    return out.index_add_(0, seg, src)
def _pad(x, pw):
    flat = tuple(v for pair in reversed(pw) for v in pair)
    return torch.nn.functional.pad(x, flat)

kernel_name = 'standalone__sliding_block_cached__sampling'

def setup_inputs():

    _w = (lambda a: (lambda t: t.to(torch.bfloat16) if t.is_floating_point() else t)(torch.as_tensor(a)))
    B, Sq, D = 8, 32, 448
    Hq, Hkv, Sk, Dh = 16, 8, 8192, 256
    assert Hq % Hkv == 0, (Hq, Hkv)
    return {
        "x": _w((lambda *s: torch.randn(*s, dtype=torch.bfloat16) * 0.8)(B, Sq, D)),
        "k_cache": _w((lambda *s: torch.randn(*s, dtype=torch.bfloat16) * 0.8)(B, Hkv, Sk, Dh)),
        "v_cache": _w((lambda *s: torch.randn(*s, dtype=torch.bfloat16) * 0.05)(B, Hkv, Sk, Dh)),
        "wq": _w((lambda *s: torch.randn(*s, dtype=torch.bfloat16) * 0.8)(D, Hq * Dh) * (D ** -0.5)),
        "wo": _w((lambda *s: torch.randn(*s, dtype=torch.bfloat16) * 0.05)(Hq * Dh, D) * ((Hq * Dh) ** -0.5)),
    }

def reference(x, k_cache, v_cache, wq, wo):
    B, Sq, D = x.shape
    Hq, Dh = 16, 256
    Hkv, Sk = k_cache.shape[1], k_cache.shape[2]
    W = min(4096, max(256, Sk // 4))
    rep = Hq // Hkv
    q = (lambda x, *d: x.permute(*d))((x @ wq).reshape(B, Sq, Hq, Dh), 0, 2, 1, 3)
    k = (lambda x, n, axis: torch.repeat_interleave(x, n, dim=axis))(k_cache[:, :, Sk - W:, :], rep, axis=1)
    v = (lambda x, n, axis: torch.repeat_interleave(x, n, dim=axis))(v_cache[:, :, Sk - W:, :], rep, axis=1)
    scores = torch.einsum("bhqd,bhkd->bhqk", q, k) * (Dh ** -0.5)
    p = _softmax(scores, axis=-1)
    o = torch.einsum("bhqk,bhkd->bhqd", p, v)
    return (lambda x, *d: x.permute(*d))(o, 0, 2, 1, 3).reshape(B, Sq, Hq * Dh) @ wo
```

```cpp
#include <cuda_runtime.h>
#include <cuda.h>
#include <cuda_bf16.h>
#include <stdint.h>

namespace {

constexpr int kB = 8, kSq = 32, kD = 448, kHq = 16, kHkv = 8, kSk = 8192, kDh = 256, kW = 2048;
constexpr uint32_t kSlot = 32768;
constexpr int kNSlot = 6;
constexpr uint32_t kQOff = kNSlot * kSlot;
constexpr uint32_t kMiscOff = kQOff + 32768;
constexpr uint32_t kSmemBytes = kMiscOff + 1024 + 1024;
constexpr int kThreads = 256;
constexpr int kPartF4 = 7 * 512;

#define DRY 1
#define KVPF 0
#define JR0 3
#define JR1 6
#define JR2 9
#define RDELAY 3
constexpr int kPosR0 = 7 + 2 * JR0 + 2, kPosR1 = 7 + 2 * JR1 + 2 + 1, kPosR2 = 7 + 2 * JR2 + 2 + 2;
constexpr int kPosWa = 40, kPosWb = 42, kPosWc = 44, kPosWd = 45, kPosEnd = 46;
constexpr uint32_t kSkipMask = (1u << JR0) | (1u << JR1) | (1u << JR2) | (1u << 14);

__device__ float4 g_part[kB * kHq * kPartF4];
__device__ unsigned g_epoch[kB];

__device__ __forceinline__ uint32_t smem_u32(const void* p) { return (uint32_t)__cvta_generic_to_shared(p); }
__device__ __forceinline__ void mbar_init(uint32_t bar, uint32_t cnt) {
  asm volatile("mbarrier.init.shared::cta.b64 [%0], %1;" ::"r"(bar), "r"(cnt) : "memory");
}
__device__ __forceinline__ void mbar_expect_tx(uint32_t bar, uint32_t bytes) {
  asm volatile("mbarrier.arrive.expect_tx.shared::cta.b64 _, [%0], %1;" ::"r"(bar), "r"(bytes) : "memory");
}
__device__ __forceinline__ void mbar_arrive(uint32_t bar) {
  asm volatile("mbarrier.arrive.shared::cta.b64 _, [%0];" ::"r"(bar) : "memory");
}
__device__ __forceinline__ void mbar_arrive_cluster(uint32_t cluster_addr) {
  asm volatile("mbarrier.arrive.release.cluster.shared::cluster.b64 _, [%0];" ::"r"(cluster_addr) : "memory");
}
__device__ __forceinline__ bool mbar_try(uint32_t bar, uint32_t parity) {
  uint32_t ok;
  asm volatile("{\n.reg .pred p;\nmbarrier.try_wait.parity.shared::cta.b64 p, [%1], %2;\nselp.u32 %0, 1, 0, p;\n}\n"
               : "=r"(ok) : "r"(bar), "r"(parity) : "memory");
  return ok != 0;
}
__device__ __forceinline__ bool mbar_test(uint32_t bar, uint32_t parity) {
  uint32_t ok;
  asm volatile("{\n.reg .pred p;\nmbarrier.test_wait.parity.shared::cta.b64 p, [%1], %2;\nselp.u32 %0, 1, 0, p;\n}\n"
               : "=r"(ok) : "r"(bar), "r"(parity) : "memory");
  return ok != 0;
}
__device__ __forceinline__ bool mbar_try_cluster(uint32_t bar, uint32_t parity) {
  uint32_t ok;
  asm volatile("{\n.reg .pred p;\nmbarrier.try_wait.parity.acquire.cluster.shared::cta.b64 p, [%1], %2;\nselp.u32 %0, 1, 0, p;\n}\n"
               : "=r"(ok) : "r"(bar), "r"(parity) : "memory");
  return ok != 0;
}
constexpr long long kSpinLimit = 4000000000ll;
constexpr uint32_t kTryLimit = 1u << 26;
__device__ __forceinline__ void mbar_wait(uint32_t bar, uint32_t parity) {
  uint32_t n = 0;
  while (!mbar_try(bar, parity)) { if (++n > kTryLimit) __trap(); }
}
__device__ __forceinline__ void mbar_wait_cluster(uint32_t bar, uint32_t parity) {
  uint32_t n = 0;
  while (!mbar_try_cluster(bar, parity)) { if (++n > kTryLimit) __trap(); }
}
__device__ __forceinline__ uint32_t mapa(uint32_t addr, uint32_t rank) {
  uint32_t r;
  asm volatile("mapa.shared::cluster.u32 %0, %1, %2;" : "=r"(r) : "r"(addr), "r"(rank));
  return r;
}
__device__ __forceinline__ void tma_3d(uint32_t dst, const CUtensorMap* tm, uint32_t bar, int c0, int c1, int c2) {
  asm volatile("cp.async.bulk.tensor.3d.shared::cluster.global.mbarrier::complete_tx::bytes [%0], [%1, {%3, %4, %5}], [%2];"
               ::"r"(dst), "l"(tm), "r"(bar), "r"(c0), "r"(c1), "r"(c2) : "memory");
}
__device__ __forceinline__ void tma_4d(uint32_t dst, const CUtensorMap* tm, uint32_t bar, int c0, int c1, int c2, int c3) {
  asm volatile("cp.async.bulk.tensor.4d.shared::cluster.global.mbarrier::complete_tx::bytes [%0], [%1, {%3, %4, %5, %6}], [%2];"
               ::"r"(dst), "l"(tm), "r"(bar), "r"(c0), "r"(c1), "r"(c2), "r"(c3) : "memory");
}
__device__ __forceinline__ void tma_prefetch_3d(const CUtensorMap* tm, int c0, int c1, int c2) {
  asm volatile("cp.async.bulk.prefetch.tensor.3d.L2.global.tile [%0, {%1, %2, %3}];" ::"l"(tm), "r"(c0), "r"(c1), "r"(c2) : "memory");
}
__device__ __forceinline__ void fence_proxy_async() { asm volatile("fence.proxy.async;" ::: "memory"); }
__device__ __forceinline__ void wgmma_fence() { asm volatile("wgmma.fence.sync.aligned;" ::: "memory"); }
__device__ __forceinline__ void wgmma_commit() { asm volatile("wgmma.commit_group.sync.aligned;" ::: "memory"); }
template <int N> __device__ __forceinline__ void wgmma_wait() { asm volatile("wgmma.wait_group.sync.aligned %0;" ::"n"(N) : "memory"); }
__device__ __forceinline__ float ex2(float x) { float y; asm("ex2.approx.ftz.f32 %0, %1;" : "=f"(y) : "f"(x)); return y; }
__device__ __forceinline__ uint32_t pack_bf16(float lo, float hi) {
  uint32_t r; asm("cvt.rn.bf16x2.f32 %0, %1, %2;" : "=r"(r) : "f"(hi), "f"(lo)); return r;
}
__device__ __forceinline__ uint64_t make_desc(uint32_t addr, uint32_t lbo, uint32_t sbo) {
  return (uint64_t)((addr & 0x3FFFF) >> 4) | ((uint64_t)(lbo >> 4) << 16) | ((uint64_t)(sbo >> 4) << 32) | (1ull << 62);
}
template <typename T> __device__ __forceinline__ void fence_regs(T& r) { asm volatile("" : "+f"(r)::"memory"); }
template <int N> __device__ __forceinline__ void fence_arr(float (&a)[N]) {
#pragma unroll
  for (int i = 0; i < N; i++) fence_regs(a[i]);
}

__device__ __forceinline__ void wgmma_ss_n64(float (&d)[32], uint64_t da, uint64_t db, int scale_d) {
  asm volatile("{\n.reg .pred p;\nsetp.ne.b32 p, %34, 0;\n"
    "wgmma.mma_async.sync.aligned.m64n64k16.f32.bf16.bf16 {%0, %1, %2, %3, %4, %5, %6, %7, %8, %9, %10, %11, %12, %13, %14, %15, %16, %17, %18, %19, %20, %21, %22, %23, %24, %25, %26, %27, %28, %29, %30, %31}, %32, %33, p, 1, 1, 0, 0;\n}\n"
    : "+f"(d[0]), "+f"(d[1]), "+f"(d[2]), "+f"(d[3]), "+f"(d[4]), "+f"(d[5]), "+f"(d[6]), "+f"(d[7]), "+f"(d[8]), "+f"(d[9]), "+f"(d[10]), "+f"(d[11]), "+f"(d[12]), "+f"(d[13]), "+f"(d[14]), "+f"(d[15]), "+f"(d[16]), "+f"(d[17]), "+f"(d[18]), "+f"(d[19]), "+f"(d[20]), "+f"(d[21]), "+f"(d[22]), "+f"(d[23]), "+f"(d[24]), "+f"(d[25]), "+f"(d[26]), "+f"(d[27]), "+f"(d[28]), "+f"(d[29]), "+f"(d[30]), "+f"(d[31])
    : "l"(da), "l"(db), "r"(scale_d));
}
__device__ __forceinline__ void wgmma_rs_n128_tb(float (&d)[64], uint32_t a0, uint32_t a1, uint32_t a2, uint32_t a3, uint64_t db) {
  asm volatile(
    "wgmma.mma_async.sync.aligned.m64n128k16.f32.bf16.bf16 {%0, %1, %2, %3, %4, %5, %6, %7, %8, %9, %10, %11, %12, %13, %14, %15, %16, %17, %18, %19, %20, %21, %22, %23, %24, %25, %26, %27, %28, %29, %30, %31, %32, %33, %34, %35, %36, %37, %38, %39, %40, %41, %42, %43, %44, %45, %46, %47, %48, %49, %50, %51, %52, %53, %54, %55, %56, %57, %58, %59, %60, %61, %62, %63}, {%64, %65, %66, %67}, %68, 1, 1, 1, 1;\n"
    : "+f"(d[0]), "+f"(d[1]), "+f"(d[2]), "+f"(d[3]), "+f"(d[4]), "+f"(d[5]), "+f"(d[6]), "+f"(d[7]), "+f"(d[8]), "+f"(d[9]), "+f"(d[10]), "+f"(d[11]), "+f"(d[12]), "+f"(d[13]), "+f"(d[14]), "+f"(d[15]), "+f"(d[16]), "+f"(d[17]), "+f"(d[18]), "+f"(d[19]), "+f"(d[20]), "+f"(d[21]), "+f"(d[22]), "+f"(d[23]), "+f"(d[24]), "+f"(d[25]), "+f"(d[26]), "+f"(d[27]), "+f"(d[28]), "+f"(d[29]), "+f"(d[30]), "+f"(d[31]), "+f"(d[32]), "+f"(d[33]), "+f"(d[34]), "+f"(d[35]), "+f"(d[36]), "+f"(d[37]), "+f"(d[38]), "+f"(d[39]), "+f"(d[40]), "+f"(d[41]), "+f"(d[42]), "+f"(d[43]), "+f"(d[44]), "+f"(d[45]), "+f"(d[46]), "+f"(d[47]), "+f"(d[48]), "+f"(d[49]), "+f"(d[50]), "+f"(d[51]), "+f"(d[52]), "+f"(d[53]), "+f"(d[54]), "+f"(d[55]), "+f"(d[56]), "+f"(d[57]), "+f"(d[58]), "+f"(d[59]), "+f"(d[60]), "+f"(d[61]), "+f"(d[62]), "+f"(d[63])
    : "r"(a0), "r"(a1), "r"(a2), "r"(a3), "l"(db));
}
__device__ __forceinline__ void wgmma_rs_n32(float (&d)[16], uint32_t a0, uint32_t a1, uint32_t a2, uint32_t a3, uint64_t db, int scale_d) {
  asm volatile("{\n.reg .pred p;\nsetp.ne.b32 p, %21, 0;\n"
    "wgmma.mma_async.sync.aligned.m64n32k16.f32.bf16.bf16 {%0, %1, %2, %3, %4, %5, %6, %7, %8, %9, %10, %11, %12, %13, %14, %15}, {%16, %17, %18, %19}, %20, p, 1, 1, 0;\n}\n"
    : "+f"(d[0]), "+f"(d[1]), "+f"(d[2]), "+f"(d[3]), "+f"(d[4]), "+f"(d[5]), "+f"(d[6]), "+f"(d[7]), "+f"(d[8]), "+f"(d[9]), "+f"(d[10]), "+f"(d[11]), "+f"(d[12]), "+f"(d[13]), "+f"(d[14]), "+f"(d[15])
    : "r"(a0), "r"(a1), "r"(a2), "r"(a3), "l"(db), "r"(scale_d));
}
__device__ __forceinline__ void wgmma_ss_n32_ta(float (&d)[16], uint64_t da, uint64_t db, int scale_d) {
  asm volatile("{\n.reg .pred p;\nsetp.ne.b32 p, %18, 0;\n"
    "wgmma.mma_async.sync.aligned.m64n32k16.f32.bf16.bf16 {%0, %1, %2, %3, %4, %5, %6, %7, %8, %9, %10, %11, %12, %13, %14, %15}, %16, %17, p, 1, 1, 1, 0;\n}\n"
    : "+f"(d[0]), "+f"(d[1]), "+f"(d[2]), "+f"(d[3]), "+f"(d[4]), "+f"(d[5]), "+f"(d[6]), "+f"(d[7]), "+f"(d[8]), "+f"(d[9]), "+f"(d[10]), "+f"(d[11]), "+f"(d[12]), "+f"(d[13]), "+f"(d[14]), "+f"(d[15])
    : "l"(da), "l"(db), "r"(scale_d));
}

#define TS(i) do {} while (0)

__global__ void __cluster_dims__(2, 1, 1) __launch_bounds__(kThreads, 1)
fused_attn_kernel(const __grid_constant__ CUtensorMap tmK, const __grid_constant__ CUtensorMap tmV,
                  const __grid_constant__ CUtensorMap tmX, const __grid_constant__ CUtensorMap tmWq,
                  const __grid_constant__ CUtensorMap tmWo, const __nv_bfloat16* __restrict__ kc,
                  const __nv_bfloat16* __restrict__ vc, __nv_bfloat16* __restrict__ out) {
  extern __shared__ uint8_t smem_raw[];
  const uint32_t sbase = (smem_u32(smem_raw) + 1023u) & ~1023u;
  const int tid = threadIdx.x, warp = tid >> 5, lane = tid & 31;
  const int cta = blockIdx.x;
  const int b = cta >> 4, hkv = (cta >> 1) & 7, s = cta & 1;
  const int h = hkv * 2 + s;
  const uint32_t misc = sbase + kMiscOff;
  const uint32_t bar_full = misc, bar_empty = misc + 48, bar_w0 = misc + 96, bar_q = misc + 104, bar_qfree = misc + 112;
  const uint32_t bar_s = misc + 128, bar_o = misc + 160, bar_wo = misc + 192;
  const uint32_t stats = misc + 256;
  const uint32_t qbase = sbase + kQOff;
  const int row0 = (b * kHkv + hkv) * kSk + (kSk - kW) + s * (kW / 2);

  if (tid == 128) {
    for (int i = 0; i < kNSlot; i++) { mbar_init(bar_full + 8 * i, 1); mbar_init(bar_empty + 8 * i, 4); }
    for (int i = 0; i < 7; i++) mbar_init(bar_wo + 8 * i, 1);
    mbar_init(bar_w0, 1); mbar_init(bar_q, 1); mbar_init(bar_qfree, 4);
    for (int i = 0; i < 4; i++) { mbar_init(bar_s + 8 * i, 1); mbar_init(bar_o + 8 * i, 1); }
    asm volatile("fence.mbarrier_init.release.cluster;" ::: "memory");
    fence_proxy_async();
    mbar_expect_tx(bar_full + 8 * 5, 7 * 4096);
    tma_3d(sbase + 5 * kSlot, &tmX, bar_full + 8 * 5, 0, b * kSq, 0);
    mbar_expect_tx(bar_w0, kSlot);
    tma_3d(qbase, &tmWq, bar_w0, 0, 0, h * 4);
#pragma unroll 1
    for (int i = 0; i < 5; i++) {
      mbar_expect_tx(bar_full + 8 * i, kSlot);
      tma_3d(sbase + i * kSlot, &tmWq, bar_full + 8 * i, 0, (i + 1) * 64, h * 4);
    }
    mbar_expect_tx(bar_q, 16384);
    for (int i = 0; i < 4; i++) { mbar_expect_tx(bar_s + 8 * i, 128); mbar_expect_tx(bar_o + 8 * i, 4096); }
    TS(26);
  } else if (tid >= 160 && tid < 163) {
    asm volatile("prefetch.tensormap [%0];" ::"l"(tid == 160 ? &tmK : tid == 161 ? &tmV : &tmWo) : "memory");
  }
  __syncthreads();
  asm volatile("barrier.cluster.arrive.relaxed.aligned;" ::: "memory");
  if (tid == 0) TS(27);

  const int wg = warp >> 2, w = warp & 3, g = lane >> 2, t = lane & 3;
  const uint32_t peer = (uint32_t)(s ^ 1);
  unsigned tag;
  float4* part = g_part + (size_t)(b * kHq + h) * kPartF4;

  auto store_part = [&](const float (&d)[16], int tile) {
#pragma unroll
    for (int i = 0; i < 4; i++) {
      const uint32_t x0 = (__float_as_uint(d[4 * i + 0]) & ~3u) | tag, x1 = (__float_as_uint(d[4 * i + 1]) & ~3u) | tag;
      const uint32_t x2 = (__float_as_uint(d[4 * i + 2]) & ~3u) | tag, x3 = (__float_as_uint(d[4 * i + 3]) & ~3u) | tag;
      asm volatile("st.relaxed.gpu.global.v4.u32 [%0], {%1, %2, %3, %4};"
                   ::"l"(part + tile * 512 + i * 128 + (tid & 127)), "r"(x0), "r"(x1), "r"(x2), "r"(x3) : "memory");
    }
  };
  auto o_desc = [&](int kk) {
    return make_desc(qbase + (uint32_t)(2 + ((kk >> 2) & 1)) * 8192u + (uint32_t)(kk >> 3) * 4096u + (uint32_t)(kk & 3) * 32u, 16, 1024);
  };
  auto oproj_smem = [&](float (&d)[16], int pos, int tile) {
    mbar_wait(bar_wo + 8 * tile, 0);
    const uint32_t ab = sbase + (uint32_t)(pos % kNSlot) * kSlot;
    wgmma_fence();
#pragma unroll
    for (int kk = 0; kk < 16; kk++) wgmma_ss_n32_ta(d, make_desc(ab + kk * 2048, 8192, 1024), o_desc(kk), kk != 0);
    wgmma_commit();
  };

  if (wg == 0) {
    {
      float a[4][16];
#pragma unroll
      for (int mt = 0; mt < 4; mt++) {
#pragma unroll
        for (int i = 0; i < 16; i++) a[mt][i] = 0.f;
        fence_arr(a[mt]);
      }
      const uint32_t xbase = sbase + 5 * kSlot;
      if (tid == 0) TS(28);
      mbar_wait(bar_full + 8 * 5, 0);
#pragma unroll 1
      for (int kt = 0; kt < 7; kt++) {
        const uint32_t sl = kt == 6 ? 0u : (uint32_t)kt - 1u;
        const uint32_t wb = kt == 0 ? qbase : sbase + sl * kSlot;
        mbar_wait(kt == 0 ? bar_w0 : bar_full + 8 * sl, kt == 6 ? 1 : 0);
        wgmma_fence();
#pragma unroll
        for (int kk = 0; kk < 4; kk++) {
          const uint64_t db = make_desc(xbase + kt * 4096 + kk * 32, 16, 1024);
#pragma unroll
          for (int mt = 0; mt < 4; mt++) wgmma_ss_n32_ta(a[mt], make_desc(wb + mt * 8192 + kk * 2048, 8192, 1024), db, 1);
        }
        wgmma_commit();
        wgmma_wait<1>();
        if (kt == 1) {
          asm volatile("barrier.cluster.wait.acquire.aligned;" ::: "memory");
          if (lane == 0) mbar_arrive_cluster(mapa(bar_qfree, peer));
        } else if (kt > 1 && lane == 0) {
          mbar_arrive(bar_empty + 8 * (kt - 2));
        }
        if (tid == 0) TS(16 + kt);
      }
      wgmma_wait<0>();
#pragma unroll
      for (int mt = 0; mt < 4; mt++) fence_arr(a[mt]);
      if (lane == 0) { mbar_arrive(bar_empty + 8 * 0); mbar_arrive(bar_empty + 8 * 5); }
      asm volatile("bar.sync 2, 128;" ::: "memory");
      const uint32_t mi = (uint32_t)lane >> 3;
      const uint32_t u = (uint32_t)(2 * w) + (mi & 1u);
#pragma unroll
      for (int mt = 0; mt < 4; mt++) {
#pragma unroll
        for (int j = 0; j < 4; j += 2) {
          const uint32_t r = (uint32_t)(32 * s + 8 * j) + 8u * (mi >> 1) + ((uint32_t)lane & 7u);
          const uint32_t addr = qbase + mt * 8192 + r * 128u + ((u ^ (r & 7u)) << 4);
          const uint32_t y0 = pack_bf16(a[mt][4 * j], a[mt][4 * j + 1]), y1 = pack_bf16(a[mt][4 * j + 2], a[mt][4 * j + 3]);
          const uint32_t y2 = pack_bf16(a[mt][4 * j + 4], a[mt][4 * j + 5]), y3 = pack_bf16(a[mt][4 * j + 6], a[mt][4 * j + 7]);
          asm volatile("stmatrix.sync.aligned.m8n8.x4.trans.shared.b16 [%0], {%1, %2, %3, %4};"
                       ::"r"(addr), "r"(y0), "r"(y1), "r"(y2), "r"(y3) : "memory");
        }
      }
      fence_proxy_async();
      asm volatile("bar.sync 2, 128;" ::: "memory");
      if (tid == 0) {
        mbar_wait_cluster(bar_qfree, 0);
        const uint32_t dst = mapa(qbase + (uint32_t)s * 4096u, peer), rb = mapa(bar_q, peer);
#pragma unroll
        for (int mt = 0; mt < 4; mt++)
          asm volatile("cp.async.bulk.shared::cluster.shared::cta.mbarrier::complete_tx::bytes [%0], [%1], 4096, [%2];"
                       ::"r"(dst + mt * 8192), "r"(qbase + (uint32_t)s * 4096u + mt * 8192), "r"(rb) : "memory");
        TS(1);
      }
      __syncwarp();
    }

    const float c = 0.0625f * 1.4426950408889634f;
    float oA[64], oB[64];
    float sc[32];
    uint32_t p[16];
#pragma unroll
    for (int i = 0; i < 64; i++) { oA[i] = 0.f; oB[i] = 0.f; }
#pragma unroll
    for (int i = 0; i < 32; i++) sc[i] = 0.f;
#pragma unroll
    for (int i = 0; i < 16; i++) p[i] = 0u;
    fence_arr(oA); fence_arr(oB); fence_arr(sc);
    float m0 = -INFINITY, m1 = -INFINITY, l0 = 0.f, l1 = 0.f;
    int slot = 1, phase = 1;
    auto advance = [&]() { if (++slot == kNSlot) { slot = 0; phase ^= 1; } };
    const uint32_t offA = (uint32_t)(s ^ 1) * 16384u, offB = (uint32_t)s * 16384u;
    auto pv_issue = [&]() {
      mbar_wait(bar_full + 8 * slot, phase);
      const uint32_t vb = sbase + slot * kSlot;
      wgmma_fence();
#pragma unroll
      for (int kk = 0; kk < 4; kk++)
        wgmma_rs_n128_tb(oA, p[4 * kk], p[4 * kk + 1], p[4 * kk + 2], p[4 * kk + 3], make_desc(vb + offA + kk * 2048, 8192, 1024));
      wgmma_commit();
#pragma unroll
      for (int kk = 0; kk < 4; kk++)
        wgmma_rs_n128_tb(oB, p[4 * kk], p[4 * kk + 1], p[4 * kk + 2], p[4 * kk + 3], make_desc(vb + offB + kk * 2048, 8192, 1024));
      wgmma_commit();
    };

    mbar_wait_cluster(bar_q, 0);
    if (tid == 0) TS(2);
#pragma unroll 1
    for (int it = 0; it < 16; it++) {
      {
        mbar_wait(bar_full + 8 * slot, phase);
        const uint32_t kb = sbase + slot * kSlot;
        wgmma_fence();
#pragma unroll
        for (int kk = 0; kk < 16; kk++) {
          const uint32_t off = (uint32_t)(kk >> 2) * 8192u + (uint32_t)(kk & 3) * 32u;
          wgmma_ss_n64(sc, make_desc(qbase + off, 16, 1024), make_desc(kb + off, 16, 1024), kk != 0);
        }
        wgmma_commit();
        wgmma_wait<0>();
        fence_arr(sc);
        if (lane == 0) mbar_arrive(bar_empty + 8 * slot);
        advance();
      }
      float mx0 = sc[0], mx1 = sc[2];
#pragma unroll
      for (int j = 0; j < 8; j++) {
        mx0 = fmaxf(mx0, fmaxf(sc[4 * j], sc[4 * j + 1]));
        mx1 = fmaxf(mx1, fmaxf(sc[4 * j + 2], sc[4 * j + 3]));
      }
      mx0 = fmaxf(mx0, __shfl_xor_sync(0xffffffffu, mx0, 1)); mx0 = fmaxf(mx0, __shfl_xor_sync(0xffffffffu, mx0, 2));
      mx1 = fmaxf(mx1, __shfl_xor_sync(0xffffffffu, mx1, 1)); mx1 = fmaxf(mx1, __shfl_xor_sync(0xffffffffu, mx1, 2));
      const float n0 = fmaxf(m0, mx0), n1 = fmaxf(m1, mx1);
      float f0 = ex2((m0 - n0) * c), f1 = ex2((m1 - n1) * c);
      m0 = n0; m1 = n1;
      const float mc0 = m0 * c, mc1 = m1 * c;
      float s0 = 0.f, s1 = 0.f;
#pragma unroll
      for (int j = 0; j < 8; j++) {
        sc[4 * j] = ex2(fmaf(sc[4 * j], c, -mc0)); sc[4 * j + 1] = ex2(fmaf(sc[4 * j + 1], c, -mc0));
        sc[4 * j + 2] = ex2(fmaf(sc[4 * j + 2], c, -mc1)); sc[4 * j + 3] = ex2(fmaf(sc[4 * j + 3], c, -mc1));
        s0 += sc[4 * j] + sc[4 * j + 1]; s1 += sc[4 * j + 2] + sc[4 * j + 3];
      }
      l0 = fmaf(l0, f0, s0); l1 = fmaf(l1, f1, s1);
      float r0 = 1.f, r1 = 1.f;
      if (it == 15) {
        l0 += __shfl_xor_sync(0xffffffffu, l0, 1); l0 += __shfl_xor_sync(0xffffffffu, l0, 2);
        l1 += __shfl_xor_sync(0xffffffffu, l1, 1); l1 += __shfl_xor_sync(0xffffffffu, l1, 2);
        const uint32_t sp = mapa(stats + (uint32_t)(16 * w + g) * 8u, peer), rb = mapa(bar_s + 8 * w, peer);
        if (t == 0) {
          asm volatile("st.async.weak.shared::cluster.mbarrier::complete_tx::bytes.v2.f32 [%0], {%1, %2}, [%3];" ::"r"(sp), "f"(m0), "f"(l0), "r"(rb) : "memory");
          asm volatile("st.async.weak.shared::cluster.mbarrier::complete_tx::bytes.v2.f32 [%0], {%1, %2}, [%3];" ::"r"(sp + 64u), "f"(m1), "f"(l1), "r"(rb) : "memory");
        }
        __syncwarp();
        asm volatile("ld.relaxed.gpu.global.u32 %0, [%1];" : "=r"(tag) : "l"(g_epoch + b) : "memory");
        if (tid == 0) TS(7);
      }
      if (it > 0) {
        if ((kSkipMask >> (it - 1)) & 1u) advance();
        pv_issue();
        if (it == 15) {
          mbar_wait_cluster(bar_s + 8 * w, 0);
          float pm0, pl0, pm1, pl1;
          asm volatile("ld.shared.v2.f32 {%0, %1}, [%2];" : "=f"(pm0), "=f"(pl0) : "r"(stats + (uint32_t)(16 * w + g) * 8u) : "memory");
          asm volatile("ld.shared.v2.f32 {%0, %1}, [%2];" : "=f"(pm1), "=f"(pl1) : "r"(stats + (uint32_t)(16 * w + g + 8) * 8u) : "memory");
          const float M0 = fmaxf(m0, pm0), M1 = fmaxf(m1, pm1);
          const float e0 = ex2((m0 - M0) * c), e1 = ex2((m1 - M1) * c);
          r0 = e0 / (l0 * e0 + pl0 * ex2((pm0 - M0) * c));
          r1 = e1 / (l1 * e1 + pl1 * ex2((pm1 - M1) * c));
          f0 *= r0; f1 *= r1;
        }
        wgmma_wait<0>();
        fence_arr(oA); fence_arr(oB);
        if (lane == 0) mbar_arrive(bar_empty + 8 * slot);
        advance();
        if (__any_sync(0xffffffffu, (f0 != 1.f) || (f1 != 1.f))) {
#pragma unroll
          for (int j = 0; j < 16; j++) {
            oA[4 * j] *= f0; oA[4 * j + 1] *= f0; oA[4 * j + 2] *= f1; oA[4 * j + 3] *= f1;
            oB[4 * j] *= f0; oB[4 * j + 1] *= f0; oB[4 * j + 2] *= f1; oB[4 * j + 3] *= f1;
          }
        }
      }
#pragma unroll
      for (int j = 0; j < 8; j++) {
        p[2 * j] = pack_bf16(sc[4 * j] * r0, sc[4 * j + 1] * r0);
        p[2 * j + 1] = pack_bf16(sc[4 * j + 2] * r1, sc[4 * j + 3] * r1);
      }
      if (tid == 0 && it == 0) TS(29);
    }
    if (tid == 0) TS(8);
    advance();
    pv_issue();
    wgmma_wait<1>();
    fence_arr(oA);
    if (tid == 0) TS(3);
    const uint32_t land = qbase + (uint32_t)w * 2048u + (uint32_t)lane * 16u;
    {
      const uint32_t dst = mapa(land, peer), rb = mapa(bar_o + 8 * w, peer);
#pragma unroll
      for (int i = 0; i < 8; i++) {
        const uint32_t y0 = pack_bf16(oA[8 * i], oA[8 * i + 1]), y1 = pack_bf16(oA[8 * i + 2], oA[8 * i + 3]);
        const uint32_t y2 = pack_bf16(oA[8 * i + 4], oA[8 * i + 5]), y3 = pack_bf16(oA[8 * i + 6], oA[8 * i + 7]);
        asm volatile("st.async.weak.shared::cluster.mbarrier::complete_tx::bytes.v4.b32 [%0], {%1, %2, %3, %4}, [%5];"
                     ::"r"(dst + (i >> 2) * 8192 + (i & 3) * 512), "r"(y0), "r"(y1), "r"(y2), "r"(y3), "r"(rb) : "memory");
      }
    }
    wgmma_wait<0>();
    fence_arr(oB);
    mbar_wait_cluster(bar_o + 8 * w, 0);
    if (tid == 0) TS(9);
    {
      const uint32_t mi = (uint32_t)lane >> 3;
      const uint32_t r = (uint32_t)(16 * w) + 8u * (mi & 1u) + ((uint32_t)lane & 7u);
#pragma unroll
      for (int i = 0; i < 8; i++) {
        uint32_t x0, x1, x2, x3;
        asm volatile("ld.shared.v4.u32 {%0, %1, %2, %3}, [%4];" : "=r"(x0), "=r"(x1), "=r"(x2), "=r"(x3)
                     : "r"(land + (i >> 2) * 8192 + (i & 3) * 512) : "memory");
        const uint32_t y0 = pack_bf16(oB[8 * i] + __uint_as_float(x0 << 16), oB[8 * i + 1] + __uint_as_float(x0 & 0xffff0000u));
        const uint32_t y1 = pack_bf16(oB[8 * i + 2] + __uint_as_float(x1 << 16), oB[8 * i + 3] + __uint_as_float(x1 & 0xffff0000u));
        const uint32_t y2 = pack_bf16(oB[8 * i + 4] + __uint_as_float(x2 << 16), oB[8 * i + 5] + __uint_as_float(x2 & 0xffff0000u));
        const uint32_t y3 = pack_bf16(oB[8 * i + 6] + __uint_as_float(x3 << 16), oB[8 * i + 7] + __uint_as_float(x3 & 0xffff0000u));
        const uint32_t u = ((uint32_t)(2 * i) + (mi >> 1)) & 7u;
        const uint32_t addr = qbase + (uint32_t)(2 + (i >> 2)) * 8192u + r * 128u + ((u ^ (r & 7u)) << 4);
        asm volatile("stmatrix.sync.aligned.m8n8.x4.shared.b16 [%0], {%1, %2, %3, %4};" ::"r"(addr), "r"(y0), "r"(y1), "r"(y2), "r"(y3) : "memory");
      }
    }
    fence_proxy_async();
    if (tid == 0) TS(30);
    float d0[16], d1[16], d2[16];
#pragma unroll
    for (int i = 0; i < 16; i++) { d0[i] = 0.f; d1[i] = 0.f; d2[i] = 0.f; }
    fence_arr(d0); fence_arr(d1); fence_arr(d2);
    tag = (tag + 1u) & 3u;
    asm volatile("bar.sync 1, 256;" ::: "memory");
    if (tid == 0) TS(4);
    oproj_smem(d0, kPosWa, 3); oproj_smem(d1, kPosWb, 4); oproj_smem(d2, kPosWc, 5);
    wgmma_wait<2>();
    fence_arr(d0); store_part(d0, 3);
    wgmma_wait<1>();
    fence_arr(d1); store_part(d1, 4);
    wgmma_wait<0>();
    fence_arr(d2);
    if (tid == 0) TS(10);
    store_part(d2, 5);
  } else {
#pragma unroll
    for (int u = 0; u < KVPF; u++) {
      const bool isv = u != 0 && !(u & 1);
      const char* src = (const char*)((isv ? vc : kc) + (size_t)(row0 + (isv ? u / 2 - 1 : (u + 1) / 2) * 64) * kDh) + (tid & 127) * 256;
      asm volatile("prefetch.global.L2 [%0];" ::"l"(src) : "memory");
      asm volatile("prefetch.global.L2 [%0];" ::"l"(src + 128) : "memory");
    }
    asm volatile("barrier.cluster.wait.acquire.aligned;" ::: "memory");
    uint32_t A0[16][4], A1[16][4], A2[16][4];
    auto grab = [&](uint32_t (&A)[16][4], int pos, int tile) {
      mbar_wait(bar_wo + 8 * tile, 0);
      const uint32_t mi = (uint32_t)lane >> 3;
      const uint32_t k = 8u * (mi >> 1) + ((uint32_t)lane & 7u);
      const uint32_t addr = sbase + (uint32_t)(pos % kNSlot) * kSlot + k * 128u + ((((uint32_t)(2 * w) + (mi & 1u)) ^ (k & 7u)) << 4);
#pragma unroll
      for (int kk = 0; kk < 16; kk++)
        asm volatile("ldmatrix.sync.aligned.m8n8.x4.trans.shared.b16 {%0, %1, %2, %3}, [%4];"
                     : "=r"(A[kk][0]), "=r"(A[kk][1]), "=r"(A[kk][2]), "=r"(A[kk][3]) : "r"(addr + kk * 2048) : "memory");
      __syncwarp();
      if (lane == 0) mbar_arrive(bar_empty + 8 * (pos % kNSlot));
    };
#pragma unroll
    for (int kk = 0; kk < 16; kk++)
#pragma unroll
      for (int i = 0; i < 4; i++) { A0[kk][i] = 0u; A1[kk][i] = 0u; A2[kk][i] = 0u; }
    int slot = 0, phase = 0;
#pragma unroll 1
    for (int pos = 6; pos < kPosEnd; pos++) {
      if (tid == 128) {
        const uint32_t fb = bar_full + 8 * slot, dst = sbase + slot * kSlot;
        mbar_wait(bar_empty + 8 * slot, phase);
        int ins = -1;
        if (pos == kPosR0) ins = 0; else if (pos == kPosR1) ins = 1; else if (pos == kPosR2) ins = 2;
        else if (pos == kPosWa) ins = 3; else if (pos == kPosWb) ins = 4; else if (pos >= kPosWc) ins = pos - kPosWc + 5;
        if (ins >= 0) {
          mbar_expect_tx(bar_wo + 8 * ins, kSlot);
          tma_4d(dst, &tmWo, bar_wo + 8 * ins, ins * 64, 0, s, hkv * 2);
          mbar_arrive(fb);
        } else {
          const int u = pos - 7 - (pos > kPosR0) - (pos > kPosR1) - (pos > kPosR2) - (pos > kPosWa) - (pos > kPosWb);
          const bool isv = u > 0 && (!(u & 1) || u == 31);
          const int j = isv ? (u == 31 ? 15 : u / 2 - 1) : (u + 1) / 2;
          mbar_expect_tx(fb, kSlot);
          tma_3d(dst, u < 0 ? &tmWq : isv ? &tmV : &tmK, fb, 0, u < 0 ? 6 * 64 : row0 + j * 64, u < 0 ? h * 4 : 0);
        }
      }
      __syncwarp();
      if (++slot == kNSlot) { slot = 0; phase ^= 1; }
      if (pos == kPosR0 + RDELAY) grab(A0, kPosR0, 0);
      if (pos == kPosR1 + RDELAY) grab(A1, kPosR1, 1);
      if (pos == kPosR2 + RDELAY) grab(A2, kPosR2, 2);
    }
    asm volatile("ld.relaxed.gpu.global.u32 %0, [%1];" : "=r"(tag) : "l"(g_epoch + b) : "memory");
    float d0[16], d1[16];
#pragma unroll
    for (int i = 0; i < 16; i++) { d0[i] = 0.f; d1[i] = 0.f; }
    fence_arr(d0); fence_arr(d1);
    tag = (tag + 1u) & 3u;
    asm volatile("bar.sync 1, 256;" ::: "memory");
    wgmma_fence();
#pragma unroll
    for (int kk = 0; kk < 16; kk++) wgmma_rs_n32(d0, A0[kk][0], A0[kk][1], A0[kk][2], A0[kk][3], o_desc(kk), kk != 0);
    wgmma_commit();
#pragma unroll
    for (int kk = 0; kk < 16; kk++) wgmma_rs_n32(d1, A1[kk][0], A1[kk][1], A1[kk][2], A1[kk][3], o_desc(kk), kk != 0);
    wgmma_commit();
    wgmma_wait<1>();
    fence_arr(d0); store_part(d0, 0);
    wgmma_fence();
#pragma unroll
    for (int kk = 0; kk < 16; kk++) wgmma_rs_n32(d0, A2[kk][0], A2[kk][1], A2[kk][2], A2[kk][3], o_desc(kk), kk != 0);
    wgmma_commit();
    wgmma_wait<1>();
    fence_arr(d1); store_part(d1, 1);
    oproj_smem(d1, kPosWd, 6);
    wgmma_wait<1>();
    fence_arr(d0); store_part(d0, 2);
    wgmma_wait<0>();
    fence_arr(d1);
    if (tid == 128) TS(11);
    store_part(d1, 6);
  }
  if (tid == 0) TS(5);

  if (tid < 224) {
    const int idx = h * 224 + tid;
    const float4* src = g_part + (size_t)b * kHq * kPartF4 + idx;
    uint4 v[16];
    uint32_t pending = 0xffffu;
    uint32_t spins = 0;
    bool first = true;
    while (true) {
      const bool many = __popc(pending) > 2 && !first;
      const uint32_t sel = many ? (pending & (0u - pending)) : pending;
#pragma unroll
      for (int j = 0; j < 16; j++) {
        if (sel & (1u << j))
          asm volatile("ld.relaxed.gpu.global.v4.u32 {%0, %1, %2, %3}, [%4];"
                       : "=r"(v[j].x), "=r"(v[j].y), "=r"(v[j].z), "=r"(v[j].w) : "l"(src + (size_t)j * kPartF4) : "memory");
      }
      uint32_t got = 0;
#pragma unroll
      for (int j = 0; j < 16; j++) {
        const uint32_t bad = ((v[j].x ^ tag) | (v[j].y ^ tag) | (v[j].z ^ tag) | (v[j].w ^ tag)) & 3u;
        if (bad == 0) got |= 1u << j;
      }
      got &= sel;
      pending &= ~got;
      if (tid == 0 && spins == 0) TS(12);
      if (!pending) break;
      first = many && got;
      if (++spins > kTryLimit) __trap();
      if (!first && many) __nanosleep(100);
    }
    if (tid == 0) TS(13);
    float r0 = 0.f, r1 = 0.f, r2 = 0.f, r3 = 0.f;
#pragma unroll
    for (int j = 0; j < 16; j++) {
      r0 += __uint_as_float(v[j].x & ~3u); r1 += __uint_as_float(v[j].y & ~3u);
      r2 += __uint_as_float(v[j].z & ~3u); r3 += __uint_as_float(v[j].w & ~3u);
    }
    const int tile = idx >> 9, i = (idx >> 7) & 3, tw = idx & 127;
    const int q = 8 * i + 2 * (tw & 3);
    const int na = 64 * tile + 16 * (tw >> 5) + ((tw & 31) >> 2), nb = na + 8;
    __nv_bfloat16* op = out + (size_t)(b * kSq + q) * kD;
    op[na] = __float2bfloat16(r0); op[kD + na] = __float2bfloat16(r1);
    op[nb] = __float2bfloat16(r2); op[kD + nb] = __float2bfloat16(r3);
  }
  if (h == 0) {
    asm volatile("bar.sync 3, 256;" ::: "memory");
    if (tid == 0) asm volatile("st.relaxed.gpu.global.u32 [%0], %1;" ::"l"(g_epoch + b), "r"(tag) : "memory");
  }
  if (tid == 0) TS(6);
}

typedef CUresult (*EncodeFn)(CUtensorMap*, CUtensorMapDataType, cuuint32_t, void*, const cuuint64_t*, const cuuint64_t*,
                             const cuuint32_t*, const cuuint32_t*, CUtensorMapInterleave, CUtensorMapSwizzle,
                             CUtensorMapL2promotion, CUtensorMapFloatOOBfill);

}

extern "C" void kernel_launch(void* const* d_in, const int* in_sizes, int n_in, void* d_out, int out_size) {
  (void)in_sizes; (void)n_in; (void)out_size;
  static CUtensorMap tmK, tmV, tmX, tmWq, tmWo;
  static const void* cached[5] = {nullptr, nullptr, nullptr, nullptr, nullptr};
  static EncodeFn enc = nullptr;
  if (!enc) {
    cudaDriverEntryPointQueryResult qr;
    cudaGetDriverEntryPoint("cuTensorMapEncodeTiled", (void**)&enc, cudaEnableDefault, &qr);
    cudaFuncSetAttribute(fused_attn_kernel, cudaFuncAttributeMaxDynamicSharedMemorySize, (int)kSmemBytes);
  }
  if (cached[0] != d_in[0] || cached[1] != d_in[1] || cached[2] != d_in[2] || cached[3] != d_in[3] || cached[4] != d_in[4]) {
    const cuuint32_t es[4] = {1, 1, 1, 1};
    {
      const cuuint64_t dims[3] = {64, (cuuint64_t)kB * kHkv * kSk, 4};
      const cuuint64_t strides[2] = {kDh * 2, 128};
      const cuuint32_t box[3] = {64, 64, 4};
      enc(&tmK, CU_TENSOR_MAP_DATA_TYPE_BFLOAT16, 3, d_in[1], dims, strides, box, es, CU_TENSOR_MAP_INTERLEAVE_NONE,
          CU_TENSOR_MAP_SWIZZLE_128B, CU_TENSOR_MAP_L2_PROMOTION_L2_256B, CU_TENSOR_MAP_FLOAT_OOB_FILL_NONE);
      enc(&tmV, CU_TENSOR_MAP_DATA_TYPE_BFLOAT16, 3, d_in[2], dims, strides, box, es, CU_TENSOR_MAP_INTERLEAVE_NONE,
          CU_TENSOR_MAP_SWIZZLE_128B, CU_TENSOR_MAP_L2_PROMOTION_L2_256B, CU_TENSOR_MAP_FLOAT_OOB_FILL_NONE);
    }
    {
      const cuuint64_t dims[3] = {64, (cuuint64_t)kB * kSq, 7};
      const cuuint64_t strides[2] = {kD * 2, 128};
      const cuuint32_t box[3] = {64, 32, 7};
      enc(&tmX, CU_TENSOR_MAP_DATA_TYPE_BFLOAT16, 3, d_in[0], dims, strides, box, es, CU_TENSOR_MAP_INTERLEAVE_NONE,
          CU_TENSOR_MAP_SWIZZLE_128B, CU_TENSOR_MAP_L2_PROMOTION_L2_128B, CU_TENSOR_MAP_FLOAT_OOB_FILL_NONE);
    }
    {
      const cuuint64_t dims[3] = {64, (cuuint64_t)kD, (cuuint64_t)kHq * kDh / 64};
      const cuuint64_t strides[2] = {(cuuint64_t)kHq * kDh * 2, 128};
      const cuuint32_t box[3] = {64, 64, 4};
      enc(&tmWq, CU_TENSOR_MAP_DATA_TYPE_BFLOAT16, 3, d_in[3], dims, strides, box, es, CU_TENSOR_MAP_INTERLEAVE_NONE,
          CU_TENSOR_MAP_SWIZZLE_128B, CU_TENSOR_MAP_L2_PROMOTION_L2_256B, CU_TENSOR_MAP_FLOAT_OOB_FILL_NONE);
    }
    {
      const cuuint64_t dims[4] = {(cuuint64_t)kD, 128, 2, (cuuint64_t)kHq};
      const cuuint64_t strides[3] = {kD * 2, (cuuint64_t)128 * kD * 2, (cuuint64_t)256 * kD * 2};
      const cuuint32_t box[4] = {64, 128, 1, 2};
      enc(&tmWo, CU_TENSOR_MAP_DATA_TYPE_BFLOAT16, 4, d_in[4], dims, strides, box, es, CU_TENSOR_MAP_INTERLEAVE_NONE,
          CU_TENSOR_MAP_SWIZZLE_128B, CU_TENSOR_MAP_L2_PROMOTION_L2_128B, CU_TENSOR_MAP_FLOAT_OOB_FILL_NONE);
    }
    for (int i = 0; i < 5; i++) cached[i] = d_in[i];
  }
  fused_attn_kernel<<<128, kThreads, kSmemBytes>>>(tmK, tmV, tmX, tmWq, tmWo, (const __nv_bfloat16*)d_in[1],
                                                    (const __nv_bfloat16*)d_in[2], (__nv_bfloat16*)d_out);
}
```

```cpp
#include <cuda_runtime.h>
#include <cuda.h>
#include <cuda_bf16.h>
#include <stdint.h>

namespace {

constexpr int kB = 8, kSq = 32, kD = 448, kHq = 16, kHkv = 8, kSk = 8192, kDh = 256, kW = 2048;
constexpr uint32_t kSlot = 32768;
constexpr int kNSlot = 6;
constexpr uint32_t kQOff = kNSlot * kSlot;
constexpr uint32_t kMiscOff = kQOff + 32768;
constexpr uint32_t kSmemBytes = kMiscOff + 1024 + 512 + 1024;
constexpr int kThreads = 256;
constexpr int kPartW = 14 * 128;

#define JW 0x01020304050607ull
#define POLLN 8
#define POLLS0 100
#define POLLS1 400
#define RDELAY 3
constexpr int kJW[7] = {(JW >> 48) & 255, (JW >> 40) & 255, (JW >> 32) & 255, (JW >> 24) & 255, (JW >> 16) & 255, (JW >> 8) & 255, JW & 255};
constexpr int kNEnt = 40;
struct Sched {
  uint16_t e[kNEnt];
  uint64_t kt, vt;
  int wslot[7], went[7];
  bool ok;
};
constexpr Sched make_sched() {
  Sched S{};
  int kind[kNEnt] = {}, idx[kNEnt] = {}, n = 0;
  kind[n] = 3; idx[n++] = 6;
  kind[n] = 0; idx[n++] = 0;
  for (int j = 0; j <= 16; j++) {
    if (j < 15) { kind[n] = 0; idx[n++] = j + 1; }
    for (int i = 0; i < 7; i++) if (kJW[i] == j) { kind[n] = 2; idx[n++] = i; }
    if (j < 16) { kind[n] = 1; idx[n++] = j; }
  }
  S.ok = n == kNEnt;
  int fifo[kNEnt + kNSlot] = {}, head = 0, tail = 0, uses[kNSlot] = {}, fulls[kNSlot] = {}, last[kNSlot] = {};
  for (int i = 0; i < kNSlot; i++) { fifo[tail++] = i; uses[i] = 1; fulls[i] = 1; last[i] = -100; }
  for (int e = 0; e < kNEnt; e++) {
    if (head == tail) { S.ok = false; break; }
    const int sl = fifo[head++];
    if (e - last[sl] <= RDELAY) S.ok = false;
    last[sl] = -100;
    S.e[e] = (uint16_t)(sl | (((uses[sl] - 1) & 1) << 3) | (kind[e] << 4) | (idx[e] << 6));
    uses[sl]++;
    if (kind[e] == 2) {
      S.wslot[idx[e]] = sl; S.went[idx[e]] = e;
      if (idx[e] < 3) { fifo[tail++] = sl; last[sl] = e; }
    } else {
      const uint64_t f = (uint64_t)(sl | ((fulls[sl] & 1) << 3)) << (4 * idx[e]);
      if (kind[e] == 0) S.kt |= f; else if (kind[e] == 1) S.vt |= f;
      fulls[sl]++;
      fifo[tail++] = sl;
    }
  }
  for (int i = 3; i < 7; i++)
    if (S.wslot[i] == (int)((S.vt >> 56) & 7) || S.wslot[i] == (int)((S.vt >> 60) & 7)) S.ok = false;
  return S;
}
constexpr Sched kS = make_sched();
static_assert(kS.ok, "ring schedule");
__constant__ Sched cS = make_sched();
constexpr uint64_t kKT = kS.kt, kVT = kS.vt;
constexpr int kSlotV14 = (int)((kVT >> 56) & 7), kSlotV15 = (int)((kVT >> 60) & 7), kParV15 = (int)(kVT >> 63);
constexpr int kEntR0 = kS.went[0], kEntR1 = kS.went[1], kEntR2 = kS.went[2];
constexpr int kW0 = kS.wslot[0], kW1 = kS.wslot[1], kW2 = kS.wslot[2], kW3 = kS.wslot[3], kW4 = kS.wslot[4], kW5 = kS.wslot[5], kW6 = kS.wslot[6];

__device__ uint4 g_part[kB * kHkv * kPartW];
__device__ unsigned g_epoch[kB];

__device__ __forceinline__ uint32_t smem_u32(const void* p) { return (uint32_t)__cvta_generic_to_shared(p); }
__device__ __forceinline__ void mbar_init(uint32_t bar, uint32_t cnt) {
  asm volatile("mbarrier.init.shared::cta.b64 [%0], %1;" ::"r"(bar), "r"(cnt) : "memory");
}
__device__ __forceinline__ void mbar_expect_tx(uint32_t bar, uint32_t bytes) {
  asm volatile("mbarrier.arrive.expect_tx.shared::cta.b64 _, [%0], %1;" ::"r"(bar), "r"(bytes) : "memory");
}
__device__ __forceinline__ void mbar_arrive(uint32_t bar) {
  asm volatile("mbarrier.arrive.shared::cta.b64 _, [%0];" ::"r"(bar) : "memory");
}
__device__ __forceinline__ void mbar_arrive_cluster(uint32_t cluster_addr) {
  asm volatile("mbarrier.arrive.relaxed.cluster.shared::cluster.b64 _, [%0];" ::"r"(cluster_addr) : "memory");
}
__device__ __forceinline__ bool mbar_try(uint32_t bar, uint32_t parity) {
  uint32_t ok;
  asm volatile("{\n.reg .pred p;\nmbarrier.try_wait.parity.shared::cta.b64 p, [%1], %2;\nselp.u32 %0, 1, 0, p;\n}\n"
               : "=r"(ok) : "r"(bar), "r"(parity) : "memory");
  return ok != 0;
}
__device__ __forceinline__ bool mbar_test(uint32_t bar, uint32_t parity) {
  uint32_t ok;
  asm volatile("{\n.reg .pred p;\nmbarrier.test_wait.parity.shared::cta.b64 p, [%1], %2;\nselp.u32 %0, 1, 0, p;\n}\n"
               : "=r"(ok) : "r"(bar), "r"(parity) : "memory");
  return ok != 0;
}
__device__ __forceinline__ bool mbar_try_cluster(uint32_t bar, uint32_t parity) {
  uint32_t ok;
  asm volatile("{\n.reg .pred p;\nmbarrier.try_wait.parity.acquire.cluster.shared::cta.b64 p, [%1], %2;\nselp.u32 %0, 1, 0, p;\n}\n"
               : "=r"(ok) : "r"(bar), "r"(parity) : "memory");
  return ok != 0;
}
constexpr long long kSpinLimit = 4000000000ll;
constexpr uint32_t kTryLimit = 1u << 26;
__device__ __forceinline__ void mbar_wait(uint32_t bar, uint32_t parity) {
  uint32_t n = 0;
  while (!mbar_try(bar, parity)) { if (++n > kTryLimit) __trap(); }
}
__device__ __forceinline__ void mbar_wait_cluster(uint32_t bar, uint32_t parity) {
  uint32_t n = 0;
  while (!mbar_try_cluster(bar, parity)) { if (++n > kTryLimit) __trap(); }
}
__device__ __forceinline__ uint32_t mapa(uint32_t addr, uint32_t rank) {
  uint32_t r;
  asm volatile("mapa.shared::cluster.u32 %0, %1, %2;" : "=r"(r) : "r"(addr), "r"(rank));
  return r;
}
__device__ __forceinline__ void tma_3d(uint32_t dst, const CUtensorMap* tm, uint32_t bar, int c0, int c1, int c2) {
  asm volatile("cp.async.bulk.tensor.3d.shared::cluster.global.mbarrier::complete_tx::bytes [%0], [%1, {%3, %4, %5}], [%2];"
               ::"r"(dst), "l"(tm), "r"(bar), "r"(c0), "r"(c1), "r"(c2) : "memory");
}
__device__ __forceinline__ void tma_4d(uint32_t dst, const CUtensorMap* tm, uint32_t bar, int c0, int c1, int c2, int c3) {
  asm volatile("cp.async.bulk.tensor.4d.shared::cluster.global.mbarrier::complete_tx::bytes [%0], [%1, {%3, %4, %5, %6}], [%2];"
               ::"r"(dst), "l"(tm), "r"(bar), "r"(c0), "r"(c1), "r"(c2), "r"(c3) : "memory");
}
__device__ __forceinline__ void st_b128(uint4* p, uint32_t x, uint32_t y, uint32_t z, uint32_t w) {
  asm volatile("{\n.reg .b128 t;\nmov.b128 t, {%1, %2, %3, %4};\nst.relaxed.gpu.global.b128 [%0], t;\n}\n"
               ::"l"(p), "r"(x), "r"(y), "r"(z), "r"(w) : "memory");
}
__device__ __forceinline__ void ld_b128(uint4& v, const uint4* p) {
  asm volatile("{\n.reg .b128 t;\nld.relaxed.gpu.global.b128 t, [%4];\nmov.b128 {%0, %1, %2, %3}, t;\n}\n"
               : "=r"(v.x), "=r"(v.y), "=r"(v.z), "=r"(v.w) : "l"(p) : "memory");
}
__device__ __forceinline__ void fence_proxy_async() { asm volatile("fence.proxy.async.shared::cta;" ::: "memory"); }
__device__ __forceinline__ void wgmma_fence() { asm volatile("wgmma.fence.sync.aligned;" ::: "memory"); }
__device__ __forceinline__ void wgmma_commit() { asm volatile("wgmma.commit_group.sync.aligned;" ::: "memory"); }
template <int N> __device__ __forceinline__ void wgmma_wait() { asm volatile("wgmma.wait_group.sync.aligned %0;" ::"n"(N) : "memory"); }
__device__ __forceinline__ float ex2(float x) { float y; asm("ex2.approx.ftz.f32 %0, %1;" : "=f"(y) : "f"(x)); return y; }
__device__ __forceinline__ float rcp(float x) { float y; asm("rcp.approx.ftz.f32 %0, %1;" : "=f"(y) : "f"(x)); return y; }
__device__ __forceinline__ uint32_t pack_bf16(float lo, float hi) {
  uint32_t r; asm("cvt.rn.bf16x2.f32 %0, %1, %2;" : "=r"(r) : "f"(hi), "f"(lo)); return r;
}
__device__ __forceinline__ uint64_t make_desc(uint32_t base16, uint32_t off, uint32_t lbo) {
  return ((uint64_t)0x40000040u << 32) | (uint64_t)(base16 + (off >> 4) + ((lbo >> 4) << 16));
}
template <typename T> __device__ __forceinline__ void fence_regs(T& r) { asm volatile("" : "+f"(r)::"memory"); }
template <int N> __device__ __forceinline__ void fence_arr(float (&a)[N]) {
#pragma unroll
  for (int i = 0; i < N; i++) fence_regs(a[i]);
}

__device__ __forceinline__ void wgmma_ss_n64(float (&d)[32], uint64_t da, uint64_t db, int scale_d) {
  asm volatile("{\n.reg .pred p;\nsetp.ne.b32 p, %34, 0;\n"
    "wgmma.mma_async.sync.aligned.m64n64k16.f32.bf16.bf16 {%0, %1, %2, %3, %4, %5, %6, %7, %8, %9, %10, %11, %12, %13, %14, %15, %16, %17, %18, %19, %20, %21, %22, %23, %24, %25, %26, %27, %28, %29, %30, %31}, %32, %33, p, 1, 1, 0, 0;\n}\n"
    : "+f"(d[0]), "+f"(d[1]), "+f"(d[2]), "+f"(d[3]), "+f"(d[4]), "+f"(d[5]), "+f"(d[6]), "+f"(d[7]), "+f"(d[8]), "+f"(d[9]), "+f"(d[10]), "+f"(d[11]), "+f"(d[12]), "+f"(d[13]), "+f"(d[14]), "+f"(d[15]), "+f"(d[16]), "+f"(d[17]), "+f"(d[18]), "+f"(d[19]), "+f"(d[20]), "+f"(d[21]), "+f"(d[22]), "+f"(d[23]), "+f"(d[24]), "+f"(d[25]), "+f"(d[26]), "+f"(d[27]), "+f"(d[28]), "+f"(d[29]), "+f"(d[30]), "+f"(d[31])
    : "l"(da), "l"(db), "r"(scale_d));
}
__device__ __forceinline__ void wgmma_rs_n128_tb(float (&d)[64], uint32_t a0, uint32_t a1, uint32_t a2, uint32_t a3, uint64_t db) {
  asm volatile(
    "wgmma.mma_async.sync.aligned.m64n128k16.f32.bf16.bf16 {%0, %1, %2, %3, %4, %5, %6, %7, %8, %9, %10, %11, %12, %13, %14, %15, %16, %17, %18, %19, %20, %21, %22, %23, %24, %25, %26, %27, %28, %29, %30, %31, %32, %33, %34, %35, %36, %37, %38, %39, %40, %41, %42, %43, %44, %45, %46, %47, %48, %49, %50, %51, %52, %53, %54, %55, %56, %57, %58, %59, %60, %61, %62, %63}, {%64, %65, %66, %67}, %68, 1, 1, 1, 1;\n"
    : "+f"(d[0]), "+f"(d[1]), "+f"(d[2]), "+f"(d[3]), "+f"(d[4]), "+f"(d[5]), "+f"(d[6]), "+f"(d[7]), "+f"(d[8]), "+f"(d[9]), "+f"(d[10]), "+f"(d[11]), "+f"(d[12]), "+f"(d[13]), "+f"(d[14]), "+f"(d[15]), "+f"(d[16]), "+f"(d[17]), "+f"(d[18]), "+f"(d[19]), "+f"(d[20]), "+f"(d[21]), "+f"(d[22]), "+f"(d[23]), "+f"(d[24]), "+f"(d[25]), "+f"(d[26]), "+f"(d[27]), "+f"(d[28]), "+f"(d[29]), "+f"(d[30]), "+f"(d[31]), "+f"(d[32]), "+f"(d[33]), "+f"(d[34]), "+f"(d[35]), "+f"(d[36]), "+f"(d[37]), "+f"(d[38]), "+f"(d[39]), "+f"(d[40]), "+f"(d[41]), "+f"(d[42]), "+f"(d[43]), "+f"(d[44]), "+f"(d[45]), "+f"(d[46]), "+f"(d[47]), "+f"(d[48]), "+f"(d[49]), "+f"(d[50]), "+f"(d[51]), "+f"(d[52]), "+f"(d[53]), "+f"(d[54]), "+f"(d[55]), "+f"(d[56]), "+f"(d[57]), "+f"(d[58]), "+f"(d[59]), "+f"(d[60]), "+f"(d[61]), "+f"(d[62]), "+f"(d[63])
    : "r"(a0), "r"(a1), "r"(a2), "r"(a3), "l"(db));
}
__device__ __forceinline__ void wgmma_rs_n32(float (&d)[16], uint32_t a0, uint32_t a1, uint32_t a2, uint32_t a3, uint64_t db, int scale_d) {
  asm volatile("{\n.reg .pred p;\nsetp.ne.b32 p, %21, 0;\n"
    "wgmma.mma_async.sync.aligned.m64n32k16.f32.bf16.bf16 {%0, %1, %2, %3, %4, %5, %6, %7, %8, %9, %10, %11, %12, %13, %14, %15}, {%16, %17, %18, %19}, %20, p, 1, 1, 0;\n}\n"
    : "+f"(d[0]), "+f"(d[1]), "+f"(d[2]), "+f"(d[3]), "+f"(d[4]), "+f"(d[5]), "+f"(d[6]), "+f"(d[7]), "+f"(d[8]), "+f"(d[9]), "+f"(d[10]), "+f"(d[11]), "+f"(d[12]), "+f"(d[13]), "+f"(d[14]), "+f"(d[15])
    : "r"(a0), "r"(a1), "r"(a2), "r"(a3), "l"(db), "r"(scale_d));
}
__device__ __forceinline__ void wgmma_ss_n32_ta(float (&d)[16], uint64_t da, uint64_t db, int scale_d) {
  asm volatile("{\n.reg .pred p;\nsetp.ne.b32 p, %18, 0;\n"
    "wgmma.mma_async.sync.aligned.m64n32k16.f32.bf16.bf16 {%0, %1, %2, %3, %4, %5, %6, %7, %8, %9, %10, %11, %12, %13, %14, %15}, %16, %17, p, 1, 1, 1, 0;\n}\n"
    : "+f"(d[0]), "+f"(d[1]), "+f"(d[2]), "+f"(d[3]), "+f"(d[4]), "+f"(d[5]), "+f"(d[6]), "+f"(d[7]), "+f"(d[8]), "+f"(d[9]), "+f"(d[10]), "+f"(d[11]), "+f"(d[12]), "+f"(d[13]), "+f"(d[14]), "+f"(d[15])
    : "l"(da), "l"(db), "r"(scale_d));
}

#define TS(i) do {} while (0)

__global__ void __cluster_dims__(2, 1, 1) __launch_bounds__(kThreads, 1)
fused_attn_kernel(const __grid_constant__ CUtensorMap tmK, const __grid_constant__ CUtensorMap tmV,
                  const __grid_constant__ CUtensorMap tmX, const __grid_constant__ CUtensorMap tmWq,
                  const __grid_constant__ CUtensorMap tmWo, __nv_bfloat16* __restrict__ out) {
  extern __shared__ uint8_t smem_raw[];
  const uint32_t sbase = (smem_u32(smem_raw) + 1023u) & ~1023u;
  const uint32_t s16 = (sbase & 0x3FFFFu) >> 4, q16 = s16 + (kQOff >> 4);
  const int tid = threadIdx.x, warp = tid >> 5, lane = tid & 31;
  const int cta = blockIdx.x;
  const int b = cta >> 4, hkv = (cta >> 1) & 7, s = cta & 1;
  const int h = hkv * 2 + s;
  const uint32_t misc = sbase + kMiscOff;
  const uint32_t bar_full = misc, bar_empty = misc + 48, bar_w0 = misc + 96, bar_q = misc + 104, bar_qfree = misc + 112;
  const uint32_t tagw = misc + 120;
  const uint32_t bar_s = misc + 128, bar_wo = misc + 160, bar_o = misc + 224;
  const uint32_t bar_m = misc + 288;
  const uint32_t stats = misc + 320, bar_x = misc + 832;
  const uint32_t qbase = sbase + kQOff;
  const int row0 = (b * kHkv + hkv) * kSk + (kSk - kW) + s * (kW / 2);

  if (tid == 128) {
    for (int i = 0; i < kNSlot; i++) mbar_init(bar_full + 8 * i, 1);
    mbar_init(bar_w0, 1);
    fence_proxy_async();
    mbar_expect_tx(bar_full + 8 * 5, 7 * 4096);
    tma_3d(sbase + 5 * kSlot, &tmX, bar_full + 8 * 5, 0, b * kSq, 0);
    mbar_expect_tx(bar_w0, kSlot);
    tma_3d(qbase, &tmWq, bar_w0, 0, 0, h * 4);
#pragma unroll 1
    for (int i = 0; i < 5; i++) {
      mbar_expect_tx(bar_full + 8 * i, kSlot);
      tma_3d(sbase + i * kSlot, &tmWq, bar_full + 8 * i, 0, (i + 1) * 64, h * 4);
    }
  } else if (tid == 160) {
    for (int i = 0; i < kNSlot; i++) mbar_init(bar_empty + 8 * i, 4);
    for (int i = 0; i < 7; i++) mbar_init(bar_wo + 8 * i, 1);
    mbar_init(bar_q, 1); mbar_init(bar_qfree, 4); mbar_init(bar_m, 4);
    for (int i = 0; i < 4; i++) mbar_init(bar_s + 8 * i, 1);
    for (int i = 0; i < 4; i++) mbar_init(bar_o + 8 * i, 1);
    for (int i = 0; i < 16; i++) mbar_init(bar_x + 8 * i, 1);
    mbar_expect_tx(bar_q, 16384);
    for (int i = 0; i < 4; i++) mbar_expect_tx(bar_s + 8 * i, 128);
    for (int i = 0; i < 4; i++) mbar_expect_tx(bar_o + 8 * i, 4096);
    for (int i = 0; i < 16; i++) mbar_expect_tx(bar_x + 8 * i, i < 12 ? 1024 : 512);
    asm volatile("fence.mbarrier_init.release.cluster;" ::: "memory");
    fence_proxy_async();
  } else if (tid >= 192 && tid < 195) {
    asm volatile("prefetch.tensormap [%0];" ::"l"(tid == 192 ? &tmK : tid == 193 ? &tmV : &tmWo) : "memory");
  }
  __syncthreads();
  asm volatile("barrier.cluster.arrive.relaxed.aligned;" ::: "memory");

  const int wg = warp >> 2, w = warp & 3, g = lane >> 2, t = lane & 3;
  const uint32_t peer = (uint32_t)(s ^ 1);
  unsigned tag;
  uint4* part = g_part + (size_t)(b * kHkv + hkv) * kPartW + s * 7 * 128 + (tid & 127);

  const uint32_t lz = sbase + (uint32_t)kSlotV14 * kSlot + (uint32_t)(tid & 127) * 16u;
  auto send_word = [&](const float* d, int L, int i) {
    const uint32_t dst = mapa(lz + (uint32_t)L * 4096u + (uint32_t)i * 2048u, peer), rb = mapa(bar_x + 8u * (uint32_t)(4 * L + w), peer);
    asm volatile("st.async.weak.shared::cluster.mbarrier::complete_tx::bytes.v4.b32 [%0], {%1, %2, %3, %4}, [%5];"
                 ::"r"(dst), "r"(pack_bf16(d[0], d[1])), "r"(pack_bf16(d[2], d[3])), "r"(pack_bf16(d[4], d[5])), "r"(pack_bf16(d[6], d[7])), "r"(rb) : "memory");
  };
  auto finish_word = [&](const float* d, int L, int i, int word) {
    uint32_t x0, x1, x2, x3;
    asm volatile("ld.shared.v4.u32 {%0, %1, %2, %3}, [%4];" : "=r"(x0), "=r"(x1), "=r"(x2), "=r"(x3)
                 : "r"(lz + (uint32_t)L * 4096u + (uint32_t)i * 2048u) : "memory");
    const uint32_t off = tag << 16;
    const uint32_t v0 = ((__float_as_uint(d[0] + __uint_as_float(x0 << 16)) - off + 0x10000u) & 0xfffe0000u) + off;
    x0 = __byte_perm(v0, pack_bf16(0.f, d[1] + __uint_as_float(x0 & 0xffff0000u)), 0x7632);
    x1 = pack_bf16(d[2] + __uint_as_float(x1 << 16), d[3] + __uint_as_float(x1 & 0xffff0000u));
    x2 = pack_bf16(d[4] + __uint_as_float(x2 << 16), d[5] + __uint_as_float(x2 & 0xffff0000u));
    x3 = pack_bf16(d[6] + __uint_as_float(x3 << 16), d[7] + __uint_as_float(x3 & 0xffff0000u));
    st_b128(part + word * 128, x0, x1, x2, x3);
  };
  auto send_tile = [&](const float (&d)[16], int L) { send_word(d, L, 0); send_word(d + 8, L, 1); };
  auto finish_tile = [&](const float (&d)[16], int L) {
    mbar_wait_cluster(bar_x + 8u * (uint32_t)(4 * L + w), 0);
    finish_word(d, L, 0, s + 2 * L); finish_word(d + 8, L, 1, s + 2 * L + 1);
  };
  auto o_desc = [&](int kk) {
    return make_desc(q16, (uint32_t)(2 + ((kk >> 2) & 1)) * 8192u + (uint32_t)(kk >> 3) * 4096u + (uint32_t)(kk & 3) * 32u, 16);
  };
  auto ldsm_tile = [&](uint32_t (&A)[16][4], int sl, int ins) {
    if ((tid & 127) == 0 && ins >= 3) TS(ins == 3 ? 15 : ins == 4 ? 17 : ins == 5 ? 20 : 22);
    mbar_wait(bar_wo + 8 * ins, 0);
    if ((tid & 127) == 0 && ins >= 3) TS(ins == 3 ? 31 : ins == 4 ? 18 : ins == 5 ? 21 : 24);
    const uint32_t mi = (uint32_t)lane >> 3;
    const uint32_t k = 8u * (mi >> 1) + ((uint32_t)lane & 7u);
    const uint32_t addr = sbase + (uint32_t)sl * kSlot + k * 128u + ((((uint32_t)(2 * w) + (mi & 1u)) ^ (k & 7u)) << 4);
#pragma unroll
    for (int kk = 0; kk < 16; kk++)
      asm volatile("ldmatrix.sync.aligned.m8n8.x4.trans.shared.b16 {%0, %1, %2, %3}, [%4];"
                   : "=r"(A[kk][0]), "=r"(A[kk][1]), "=r"(A[kk][2]), "=r"(A[kk][3]) : "r"(addr + kk * 2048) : "memory");
  };
  auto oproj = [&](float (&d)[16], const uint32_t (&A)[16][4]) {
#pragma unroll
    for (int kk = 0; kk < 16; kk++) wgmma_rs_n32(d, A[kk][0], A[kk][1], A[kk][2], A[kk][3], o_desc(kk), kk != 0);
    wgmma_commit();
  };

  if (wg == 0) {
    {
      float a[4][16];
#pragma unroll
      for (int mt = 0; mt < 4; mt++) {
#pragma unroll
        for (int i = 0; i < 16; i++) a[mt][i] = 0.f;
        fence_arr(a[mt]);
      }
      mbar_wait(bar_full + 8 * 5, 0);
#pragma unroll 1
      for (int kt = 0; kt < 7; kt++) {
        const uint32_t sl = kt == 6 ? 0u : (uint32_t)kt - 1u;
        const uint32_t wb = kt == 0 ? q16 : s16 + sl * (kSlot >> 4);
        const uint32_t xb = s16 + ((5 * kSlot) >> 4) + (uint32_t)kt * 256u;
        mbar_wait(kt == 0 ? bar_w0 : bar_full + 8 * sl, kt == 6 ? 1 : 0);
        wgmma_fence();
#pragma unroll
        for (int kk = 0; kk < 4; kk++) {
#pragma unroll
          for (int mt = 0; mt < 4; mt++)
            wgmma_ss_n32_ta(a[mt], make_desc(wb, mt * 8192 + kk * 2048, 8192), make_desc(xb, kk * 32, 16), 1);
        }
        wgmma_commit();
        wgmma_wait<1>();
        if (kt == 1) {
          asm volatile("barrier.cluster.wait.acquire.aligned;" ::: "memory");
          if (lane == 0) mbar_arrive_cluster(mapa(bar_qfree, peer));
        } else if (kt > 1 && lane == 0) {
          mbar_arrive(bar_empty + 8 * (kt - 2));
        }
      }
      wgmma_wait<0>();
#pragma unroll
      for (int mt = 0; mt < 4; mt++) fence_arr(a[mt]);
      if (lane == 0) { mbar_arrive(bar_empty + 8 * 0); mbar_arrive(bar_empty + 8 * 5); }
      asm volatile("bar.sync 2, 128;" ::: "memory");
      const uint32_t mi = (uint32_t)lane >> 3;
      const uint32_t u = (uint32_t)(2 * w) + (mi & 1u);
#pragma unroll
      for (int mt = 0; mt < 4; mt++) {
#pragma unroll
        for (int j = 0; j < 4; j += 2) {
          const uint32_t r = (uint32_t)(32 * s + 8 * j) + 8u * (mi >> 1) + ((uint32_t)lane & 7u);
          const uint32_t addr = qbase + mt * 8192 + r * 128u + ((u ^ (r & 7u)) << 4);
          const uint32_t y0 = pack_bf16(a[mt][4 * j], a[mt][4 * j + 1]), y1 = pack_bf16(a[mt][4 * j + 2], a[mt][4 * j + 3]);
          const uint32_t y2 = pack_bf16(a[mt][4 * j + 4], a[mt][4 * j + 5]), y3 = pack_bf16(a[mt][4 * j + 6], a[mt][4 * j + 7]);
          asm volatile("stmatrix.sync.aligned.m8n8.x4.trans.shared.b16 [%0], {%1, %2, %3, %4};"
                       ::"r"(addr), "r"(y0), "r"(y1), "r"(y2), "r"(y3) : "memory");
        }
      }
      fence_proxy_async();
      asm volatile("bar.sync 2, 128;" ::: "memory");
      if (tid == 0) {
        mbar_wait_cluster(bar_qfree, 0);
        const uint32_t dst = mapa(qbase + (uint32_t)s * 4096u, peer), rb = mapa(bar_q, peer);
#pragma unroll
        for (int mt = 0; mt < 4; mt++)
          asm volatile("cp.async.bulk.shared::cluster.shared::cta.mbarrier::complete_tx::bytes [%0], [%1], 4096, [%2];"
                       ::"r"(dst + mt * 8192), "r"(qbase + (uint32_t)s * 4096u + mt * 8192), "r"(rb) : "memory");
      }
      __syncwarp();
    }

    const float c = 0.0625f * 1.4426950408889634f;
    float oA[64], oB[64];
    float sc[32];
    uint32_t p[16];
#pragma unroll
    for (int i = 0; i < 64; i++) { oA[i] = 0.f; oB[i] = 0.f; }
#pragma unroll
    for (int i = 0; i < 32; i++) sc[i] = 0.f;
#pragma unroll
    for (int i = 0; i < 16; i++) p[i] = 0u;
    fence_arr(oA); fence_arr(oB); fence_arr(sc);
    float m0 = -INFINITY, m1 = -INFINITY, l0 = 0.f, l1 = 0.f;
    const uint32_t offA = (uint32_t)(s ^ 1) * 1024u, offB = (uint32_t)s * 1024u;
    auto pv_issue = [&](uint32_t vb) {
      wgmma_fence();
#pragma unroll
      for (int kk = 0; kk < 4; kk++)
        wgmma_rs_n128_tb(oA, p[4 * kk], p[4 * kk + 1], p[4 * kk + 2], p[4 * kk + 3], make_desc(vb + offA, kk * 2048, 8192));
      wgmma_commit();
#pragma unroll
      for (int kk = 0; kk < 4; kk++)
        wgmma_rs_n128_tb(oB, p[4 * kk], p[4 * kk + 1], p[4 * kk + 2], p[4 * kk + 3], make_desc(vb + offB, kk * 2048, 8192));
      wgmma_commit();
    };

    mbar_wait_cluster(bar_q, 0);
#pragma unroll 1
    for (int it = 0; it < 16; it++) {
      const uint32_t ke = (uint32_t)(kKT >> (4 * it)), ks = ke & 7u;
      if (tid == 0 && it >= 14) TS(it == 15 ? 26 : 2);
      mbar_wait(bar_full + 8 * ks, (ke >> 3) & 1u);
      if (tid == 0 && it >= 14) TS(it == 15 ? 27 : 1);
      {
        const uint32_t kb = s16 + ks * (kSlot >> 4);
        wgmma_fence();
#pragma unroll
        for (int kk = 0; kk < 16; kk++) {
          const uint32_t off = (uint32_t)(kk >> 2) * 8192u + (uint32_t)(kk & 3) * 32u;
          wgmma_ss_n64(sc, make_desc(q16, off, 16), make_desc(kb, off, 16), kk != 0);
        }
        wgmma_commit();
      }
      uint32_t vs = ks;
      bool held = it > 0;
      if (it > 0) {
        const uint32_t ve = (uint32_t)(kVT >> (4 * it - 4)), phase = (ve >> 3) & 1u;
        vs = ve & 7u;
        if (!__all_sync(0xffffffffu, mbar_test(bar_full + 8 * vs, phase))) {
          wgmma_wait<0>();
          if (lane == 0) mbar_arrive(bar_empty + 8 * ks);
          held = false;
          mbar_wait(bar_full + 8 * vs, phase);
        }
        if (tid == 0 && it >= 14) TS(it == 15 ? 28 : 23);
      }
      pv_issue(s16 + vs * (kSlot >> 4));
      wgmma_wait<2>();
      fence_arr(sc);
      if (lane == 0 && held) mbar_arrive(bar_empty + 8 * ks);
      float mx0 = sc[0], mx1 = sc[2];
#pragma unroll
      for (int j = 0; j < 8; j++) {
        mx0 = fmaxf(mx0, fmaxf(sc[4 * j], sc[4 * j + 1]));
        mx1 = fmaxf(mx1, fmaxf(sc[4 * j + 2], sc[4 * j + 3]));
      }
      mx0 = fmaxf(mx0, __shfl_xor_sync(0xffffffffu, mx0, 1)); mx0 = fmaxf(mx0, __shfl_xor_sync(0xffffffffu, mx0, 2));
      mx1 = fmaxf(mx1, __shfl_xor_sync(0xffffffffu, mx1, 1)); mx1 = fmaxf(mx1, __shfl_xor_sync(0xffffffffu, mx1, 2));
      const float n0 = fmaxf(m0, mx0), n1 = fmaxf(m1, mx1);
      const float f0 = ex2((m0 - n0) * c), f1 = ex2((m1 - n1) * c);
      m0 = n0; m1 = n1;
      const float mc0 = m0 * c, mc1 = m1 * c;
      float s0 = 0.f, s1 = 0.f;
#pragma unroll
      for (int j = 0; j < 8; j++) {
        sc[4 * j] = ex2(fmaf(sc[4 * j], c, -mc0)); sc[4 * j + 1] = ex2(fmaf(sc[4 * j + 1], c, -mc0));
        sc[4 * j + 2] = ex2(fmaf(sc[4 * j + 2], c, -mc1)); sc[4 * j + 3] = ex2(fmaf(sc[4 * j + 3], c, -mc1));
        s0 += sc[4 * j] + sc[4 * j + 1]; s1 += sc[4 * j + 2] + sc[4 * j + 3];
      }
      l0 = fmaf(l0, f0, s0); l1 = fmaf(l1, f1, s1);
      if (it == 15) {
        l0 += __shfl_xor_sync(0xffffffffu, l0, 1); l0 += __shfl_xor_sync(0xffffffffu, l0, 2);
        l1 += __shfl_xor_sync(0xffffffffu, l1, 1); l1 += __shfl_xor_sync(0xffffffffu, l1, 2);
        const uint32_t sp = mapa(stats + (uint32_t)(16 * w + g) * 8u, peer), rb = mapa(bar_s + 8 * w, peer);
        if (t == 0) {
          asm volatile("st.async.weak.shared::cluster.mbarrier::complete_tx::bytes.v2.f32 [%0], {%1, %2}, [%3];" ::"r"(sp), "f"(m0), "f"(l0), "r"(rb) : "memory");
          asm volatile("st.async.weak.shared::cluster.mbarrier::complete_tx::bytes.v2.f32 [%0], {%1, %2}, [%3];" ::"r"(sp + 64u), "f"(m1), "f"(l1), "r"(rb) : "memory");
        }
        __syncwarp();
        if (tid == 0) TS(7);
      }
      wgmma_wait<0>();
      fence_arr(oA); fence_arr(oB);
      if (lane == 0) mbar_arrive(bar_empty + 8 * vs);
      if (__any_sync(0xffffffffu, (f0 != 1.f) || (f1 != 1.f))) {
#pragma unroll
        for (int j = 0; j < 16; j++) {
          oA[4 * j] *= f0; oA[4 * j + 1] *= f0; oA[4 * j + 2] *= f1; oA[4 * j + 3] *= f1;
          oB[4 * j] *= f0; oB[4 * j + 1] *= f0; oB[4 * j + 2] *= f1; oB[4 * j + 3] *= f1;
        }
      }
#pragma unroll
      for (int j = 0; j < 8; j++) {
        p[2 * j] = pack_bf16(sc[4 * j], sc[4 * j + 1]);
        p[2 * j + 1] = pack_bf16(sc[4 * j + 2], sc[4 * j + 3]);
      }
    }
    if (tid == 0) TS(8);
    mbar_wait(bar_full + 8 * kSlotV15, kParV15);
    if (tid == 0) TS(29);
    const uint32_t v15 = s16 + kSlotV15 * (kSlot >> 4);
    wgmma_fence();
#pragma unroll
    for (int kk = 0; kk < 4; kk++)
      wgmma_rs_n128_tb(oA, p[4 * kk], p[4 * kk + 1], p[4 * kk + 2], p[4 * kk + 3], make_desc(v15 + offA, kk * 2048, 8192));
    wgmma_commit();
    float r0, r1, u0, u1;
    {
      mbar_wait_cluster(bar_s + 8 * w, 0);
      float pm0, pl0, pm1, pl1;
      asm volatile("ld.shared.v2.f32 {%0, %1}, [%2];" : "=f"(pm0), "=f"(pl0) : "r"(stats + (uint32_t)(16 * w + g) * 8u) : "memory");
      asm volatile("ld.shared.v2.f32 {%0, %1}, [%2];" : "=f"(pm1), "=f"(pl1) : "r"(stats + (uint32_t)(16 * w + g + 8) * 8u) : "memory");
      const float M0 = fmaxf(m0, pm0), M1 = fmaxf(m1, pm1);
      const float e0 = ex2((m0 - M0) * c), e1 = ex2((m1 - M1) * c);
      const float g0 = ex2((pm0 - M0) * c), g1 = ex2((pm1 - M1) * c);
      const float i0 = rcp(l0 * e0 + pl0 * g0), i1 = rcp(l1 * e1 + pl1 * g1);
      r0 = e0 * i0; r1 = e1 * i1; u0 = g0 * i0; u1 = g1 * i1;
      fence_regs(r0); fence_regs(r1); fence_regs(u0); fence_regs(u1);
      mbar_wait(bar_w0, 0);
    }
    const uint32_t land = qbase + (uint32_t)w * 2048u + (uint32_t)lane * 16u;
    wgmma_wait<0>();
    fence_arr(oA);
    if (tid == 0) TS(3);
    {
      const uint32_t dst = mapa(land, peer), rb = mapa(bar_o + 8 * w, peer);
#pragma unroll
      for (int i = 0; i < 8; i++) {
        const uint32_t y0 = pack_bf16(oA[8 * i], oA[8 * i + 1]), y1 = pack_bf16(oA[8 * i + 2], oA[8 * i + 3]);
        const uint32_t y2 = pack_bf16(oA[8 * i + 4], oA[8 * i + 5]), y3 = pack_bf16(oA[8 * i + 6], oA[8 * i + 7]);
        asm volatile("st.async.weak.shared::cluster.mbarrier::complete_tx::bytes.v4.b32 [%0], {%1, %2, %3, %4}, [%5];"
                     ::"r"(dst + (i >> 2) * 8192 + (i & 3) * 512), "r"(y0), "r"(y1), "r"(y2), "r"(y3), "r"(rb) : "memory");
      }
    }
    if (tid == 0) TS(14);
    wgmma_fence();
#pragma unroll
    for (int kk = 0; kk < 4; kk++)
      wgmma_rs_n128_tb(oB, p[4 * kk], p[4 * kk + 1], p[4 * kk + 2], p[4 * kk + 3], make_desc(v15 + offB, kk * 2048, 8192));
    wgmma_commit();
    uint32_t B0[16][4], B1[16][4];
    ldsm_tile(B0, kW3, 3);
    wgmma_wait<0>();
    fence_arr(oB);
#pragma unroll
    for (int j = 0; j < 16; j++) { oB[4 * j] *= r0; oB[4 * j + 1] *= r0; oB[4 * j + 2] *= r1; oB[4 * j + 3] *= r1; }
    fence_arr(oB);
    mbar_wait_cluster(bar_o + 8 * w, 0);
    if (tid == 0) TS(9);
    {
      const uint32_t mi = (uint32_t)lane >> 3;
      const uint32_t r = (uint32_t)(16 * w) + 8u * (mi & 1u) + ((uint32_t)lane & 7u);
      uint32_t x[8][4];
#pragma unroll
      for (int i = 0; i < 8; i++)
        asm volatile("ld.shared.v4.u32 {%0, %1, %2, %3}, [%4];" : "=r"(x[i][0]), "=r"(x[i][1]), "=r"(x[i][2]), "=r"(x[i][3])
                     : "r"(land + (i >> 2) * 8192 + (i & 3) * 512) : "memory");
#pragma unroll
      for (int i = 0; i < 8; i++) {
#pragma unroll
        for (int e = 0; e < 4; e++) {
          const float uu = (e & 1) ? u1 : u0;
          x[i][e] = pack_bf16(fmaf(__uint_as_float(x[i][e] << 16), uu, oB[8 * i + 2 * e]),
                              fmaf(__uint_as_float(x[i][e] & 0xffff0000u), uu, oB[8 * i + 2 * e + 1]));
        }
        const uint32_t u = ((uint32_t)(2 * i) + (mi >> 1)) & 7u;
        const uint32_t addr = qbase + (uint32_t)(2 + (i >> 2)) * 8192u + r * 128u + ((u ^ (r & 7u)) << 4);
        asm volatile("stmatrix.sync.aligned.m8n8.x4.shared.b16 [%0], {%1, %2, %3, %4};"
                     ::"r"(addr), "r"(x[i][0]), "r"(x[i][1]), "r"(x[i][2]), "r"(x[i][3]) : "memory");
      }
    }
    fence_proxy_async();
    __syncwarp();
    if (lane == 0) mbar_arrive(bar_m);
    if (tid == 0) TS(30);
    ldsm_tile(B1, kW4, 4);
    float d3[16], d4[16];
#pragma unroll
    for (int i = 0; i < 16; i++) { d3[i] = 0.f; d4[i] = 0.f; }
    fence_arr(d3); fence_arr(d4);
    asm volatile("ld.shared.u32 %0, [%1];" : "=r"(tag) : "r"(tagw) : "memory");
    mbar_wait(bar_m, 0);
    if (tid == 0) TS(4);
    wgmma_fence();
    oproj(d3, B0);
    oproj(d4, B1);
    wgmma_wait<1>();
    fence_arr(d3);
    send_tile(d3, 2);
    ldsm_tile(B0, kW5, 5);
    wgmma_fence();
    oproj(d3, B0);
    wgmma_wait<1>();
    fence_arr(d4);
    finish_tile(d4, 0);
    mbar_wait(bar_m, 0);
    wgmma_wait<0>();
    fence_arr(d3);
    if (tid == 0) TS(10);
    finish_tile(d3, 1);
  } else {
    asm volatile("barrier.cluster.wait.acquire.aligned;" ::: "memory");
    uint32_t A0[16][4], A1[16][4], A2[16][4];
    auto grab = [&](uint32_t (&A)[16][4], int sl, int ins) {
      ldsm_tile(A, sl, ins);
      __syncwarp();
      if (lane == 0) mbar_arrive(bar_empty + 8 * sl);
    };
#pragma unroll
    for (int kk = 0; kk < 16; kk++)
#pragma unroll
      for (int i = 0; i < 4; i++) { A0[kk][i] = 0u; A1[kk][i] = 0u; A2[kk][i] = 0u; }
    if (tid == 160) {
      asm volatile("ld.relaxed.gpu.global.u32 %0, [%1];" : "=r"(tag) : "l"(g_epoch + b) : "memory");
      asm volatile("st.shared.u32 [%0], %1;" ::"r"(tagw), "r"((tag + 1u) & 1u) : "memory");
    }
    __syncwarp();
#pragma unroll 1
    for (int e = 0; e < kNEnt; e++) {
      if (tid == 128) {
        const uint32_t en = cS.e[e], slot = en & 7u, kind = (en >> 4) & 3u;
        const int idx = (int)(en >> 6);
        const uint32_t fb = bar_full + 8 * slot, dst = sbase + slot * kSlot;
        mbar_wait(bar_empty + 8 * slot, (en >> 3) & 1u);
        if (kind == 2) {
          mbar_expect_tx(bar_wo + 8 * idx, kSlot);
          const int tile = idx == 0 ? 3 : idx <= 3 ? 4 * (s ^ 1) + idx - 1 : 4 * s + idx - 4;
          tma_4d(dst, &tmWo, bar_wo + 8 * idx, tile * 64, 0, s, hkv * 2);
        } else {
          mbar_expect_tx(fb, kSlot);
          tma_3d(dst, kind == 3 ? &tmWq : kind ? &tmV : &tmK, fb, 0, (kind == 3 ? 0 : row0) + idx * 64, kind == 3 ? h * 4 : 0);
        }
      }
      __syncwarp();
      if (e == kEntR0 + RDELAY) grab(A0, kW0, 0);
      if (e == kEntR1 + RDELAY) grab(A1, kW1, 1);
      if (e == kEntR2 + RDELAY) grab(A2, kW2, 2);
    }
    float d0[16], d1[16];
#pragma unroll
    for (int i = 0; i < 16; i++) { d0[i] = 0.f; d1[i] = 0.f; }
    fence_arr(d0); fence_arr(d1);
    mbar_wait(bar_m, 0);
    asm volatile("ld.shared.u32 %0, [%1];" : "=r"(tag) : "r"(tagw) : "memory");
    wgmma_fence();
    oproj(d0, A0);
    oproj(d1, A1);
    wgmma_wait<1>();
    fence_arr(d0);
    float mh[8], mp[8];
#pragma unroll
    for (int i = 0; i < 8; i++) { mh[i] = s ? d0[8 + i] : d0[i]; mp[i] = s ? d0[i] : d0[8 + i]; }
    send_word(mp, 3, 0);
    fence_arr(mh);
    ldsm_tile(A0, kW6, 6);
    wgmma_wait<0>();
    fence_arr(d1);
    send_tile(d1, 0);
    wgmma_fence();
    oproj(d0, A2);
    oproj(d1, A0);
    wgmma_wait<1>();
    fence_arr(d0);
    send_tile(d0, 1);
    mbar_wait_cluster(bar_x + 8u * (uint32_t)(12 + w), 0);
    finish_word(mh, 3, 0, s ? 0 : 6);
    mbar_wait(bar_m, 0);
    wgmma_wait<0>();
    fence_arr(d1);
    if (tid == 128) TS(11);
    finish_tile(d1, 2);
  }
  if (tid == 0) TS(5);
  if (tid == 128) TS(19);

  if (h < 14) {
    const int hw = lane >> 4, tw = warp * 16 + (lane & 15);
    const uint4* src0 = g_part + (size_t)(b * kHkv) * kPartW + h * 128;
    const uint4* src = src0 + (size_t)(hw * 4) * kPartW + tw;
    uint4 v[4];
    uint32_t pending = 0xffu, sel = 0xffu;
    uint32_t spins = 0;
    while (true) {
      const uint32_t mine = sel >> (4 * hw);
#pragma unroll
      for (int j = 0; j < 4; j++)
        if (mine & (1u << j)) ld_b128(v[j], src + (size_t)j * kPartW);
      if (tid == 0 && spins == 0) TS(16);
      uint32_t bad = 0;
#pragma unroll
      for (int j = 0; j < 4; j++) bad |= ((v[j].x ^ tag) & 1u) << j;
      bad = __reduce_or_sync(0xffffffffu, bad << (4 * hw));
      pending &= bad | ~sel;
      if (tid == 0 && spins == 0) TS(12);
      if (!pending) break;
      if (++spins > kTryLimit) __trap();
      sel = pending;
      if (__popc(pending) > POLLN) {
        do {
          __nanosleep(POLLS0);
          uint32_t wd = ~tag;
          if ((pending >> lane) & 1u)
            asm volatile("ld.relaxed.gpu.global.u32 %0, [%1];" : "=r"(wd) : "l"(src0 + (size_t)lane * kPartW + warp * 16) : "memory");
          sel = __ballot_sync(0xffffffffu, ((wd ^ tag) & 1u) == 0);
          if (++spins > kTryLimit) __trap();
        } while (!sel);
      }
    }
    if (tid == 0) TS(13);
    if (tid == 128) TS(25);
    float r[8];
#pragma unroll
    for (int e = 0; e < 8; e++) r[e] = 0.f;
#pragma unroll
    for (int j = 0; j < 4; j++) {
      r[0] += __uint_as_float(v[j].x << 16); r[1] += __uint_as_float(v[j].x & 0xffff0000u);
      r[2] += __uint_as_float(v[j].y << 16); r[3] += __uint_as_float(v[j].y & 0xffff0000u);
      r[4] += __uint_as_float(v[j].z << 16); r[5] += __uint_as_float(v[j].z & 0xffff0000u);
      r[6] += __uint_as_float(v[j].w << 16); r[7] += __uint_as_float(v[j].w & 0xffff0000u);
    }
    const float y0 = (hw ? r[4] : r[0]) + __shfl_xor_sync(0xffffffffu, hw ? r[0] : r[4], 16);
    const float y1 = (hw ? r[5] : r[1]) + __shfl_xor_sync(0xffffffffu, hw ? r[1] : r[5], 16);
    const float y2 = (hw ? r[6] : r[2]) + __shfl_xor_sync(0xffffffffu, hw ? r[2] : r[6], 16);
    const float y3 = (hw ? r[7] : r[3]) + __shfl_xor_sync(0xffffffffu, hw ? r[3] : r[7], 16);
    if (h == 0 && tid == 64) asm volatile("st.relaxed.gpu.global.u32 [%0], %1;" ::"l"(g_epoch + b), "r"(tag) : "memory");
    const int q = 8 * (2 * s + hw) + 2 * (tw & 3);
    const int na = 64 * hkv + 16 * (tw >> 5) + ((tw & 31) >> 2), nb = na + 8;
    __nv_bfloat16* op = out + (size_t)(b * kSq + q) * kD;
    op[na] = __float2bfloat16(y0); op[kD + na] = __float2bfloat16(y1);
    op[nb] = __float2bfloat16(y2); op[kD + nb] = __float2bfloat16(y3);
  }
  if (tid == 0) TS(6);
}

typedef CUresult (*EncodeFn)(CUtensorMap*, CUtensorMapDataType, cuuint32_t, void*, const cuuint64_t*, const cuuint64_t*,
                             const cuuint32_t*, const cuuint32_t*, CUtensorMapInterleave, CUtensorMapSwizzle,
                             CUtensorMapL2promotion, CUtensorMapFloatOOBfill);

}

extern "C" void kernel_launch(void* const* d_in, const int* in_sizes, int n_in, void* d_out, int out_size) {
  (void)in_sizes; (void)n_in; (void)out_size;
  static CUtensorMap tmK, tmV, tmX, tmWq, tmWo;
  static const void* cached[5] = {nullptr, nullptr, nullptr, nullptr, nullptr};
  static EncodeFn enc = nullptr;
  if (!enc) {
    cudaDriverEntryPointQueryResult qr;
    cudaGetDriverEntryPoint("cuTensorMapEncodeTiled", (void**)&enc, cudaEnableDefault, &qr);
    cudaFuncSetAttribute(fused_attn_kernel, cudaFuncAttributeMaxDynamicSharedMemorySize, (int)kSmemBytes);
  }
  if (cached[0] != d_in[0] || cached[1] != d_in[1] || cached[2] != d_in[2] || cached[3] != d_in[3] || cached[4] != d_in[4]) {
    const cuuint32_t es[4] = {1, 1, 1, 1};
    {
      const cuuint64_t dims[3] = {64, (cuuint64_t)kB * kHkv * kSk, 4};
      const cuuint64_t strides[2] = {kDh * 2, 128};
      const cuuint32_t box[3] = {64, 64, 4};
      enc(&tmK, CU_TENSOR_MAP_DATA_TYPE_BFLOAT16, 3, d_in[1], dims, strides, box, es, CU_TENSOR_MAP_INTERLEAVE_NONE,
          CU_TENSOR_MAP_SWIZZLE_128B, CU_TENSOR_MAP_L2_PROMOTION_L2_256B, CU_TENSOR_MAP_FLOAT_OOB_FILL_NONE);
      enc(&tmV, CU_TENSOR_MAP_DATA_TYPE_BFLOAT16, 3, d_in[2], dims, strides, box, es, CU_TENSOR_MAP_INTERLEAVE_NONE,
          CU_TENSOR_MAP_SWIZZLE_128B, CU_TENSOR_MAP_L2_PROMOTION_L2_256B, CU_TENSOR_MAP_FLOAT_OOB_FILL_NONE);
    }
    {
      const cuuint64_t dims[3] = {64, (cuuint64_t)kB * kSq, 7};
      const cuuint64_t strides[2] = {kD * 2, 128};
      const cuuint32_t box[3] = {64, 32, 7};
      enc(&tmX, CU_TENSOR_MAP_DATA_TYPE_BFLOAT16, 3, d_in[0], dims, strides, box, es, CU_TENSOR_MAP_INTERLEAVE_NONE,
          CU_TENSOR_MAP_SWIZZLE_128B, CU_TENSOR_MAP_L2_PROMOTION_L2_128B, CU_TENSOR_MAP_FLOAT_OOB_FILL_NONE);
    }
    {
      const cuuint64_t dims[3] = {64, (cuuint64_t)kD, (cuuint64_t)kHq * kDh / 64};
      const cuuint64_t strides[2] = {(cuuint64_t)kHq * kDh * 2, 128};
      const cuuint32_t box[3] = {64, 64, 4};
      enc(&tmWq, CU_TENSOR_MAP_DATA_TYPE_BFLOAT16, 3, d_in[3], dims, strides, box, es, CU_TENSOR_MAP_INTERLEAVE_NONE,
          CU_TENSOR_MAP_SWIZZLE_128B, CU_TENSOR_MAP_L2_PROMOTION_L2_256B, CU_TENSOR_MAP_FLOAT_OOB_FILL_NONE);
    }
    {
      const cuuint64_t dims[4] = {(cuuint64_t)kD, 128, 2, (cuuint64_t)kHq};
      const cuuint64_t strides[3] = {kD * 2, (cuuint64_t)128 * kD * 2, (cuuint64_t)256 * kD * 2};
      const cuuint32_t box[4] = {64, 128, 1, 2};
      enc(&tmWo, CU_TENSOR_MAP_DATA_TYPE_BFLOAT16, 4, d_in[4], dims, strides, box, es, CU_TENSOR_MAP_INTERLEAVE_NONE,
          CU_TENSOR_MAP_SWIZZLE_128B, CU_TENSOR_MAP_L2_PROMOTION_L2_128B, CU_TENSOR_MAP_FLOAT_OOB_FILL_NONE);
    }
    for (int i = 0; i < 5; i++) cached[i] = d_in[i];
  }
  fused_attn_kernel<<<128, kThreads, kSmemBytes>>>(tmK, tmV, tmX, tmWq, tmWo, (__nv_bfloat16*)d_out);
}
```

```cpp
#include <cuda_runtime.h>
#include <cuda.h>
#include <cuda_bf16.h>
#include <stdint.h>
#include <type_traits>

namespace {

constexpr int kB = 8, kSq = 32, kD = 448, kHq = 16, kHkv = 8, kSk = 8192, kDh = 256, kW = 2048;
constexpr uint32_t kSlot = 32768;
constexpr int kNSlot = 6;
constexpr uint32_t kQOff = kNSlot * kSlot;
constexpr uint32_t kMiscOff = kQOff + 32768;
constexpr uint32_t kSmemBytes = kMiscOff + 1024 + 512 + 1024;
constexpr int kThreads = 256;
constexpr int kPartW = 14 * 128;

#define JW 0x01020304050610ull
#define DLO 64
#define DHI 64
#define ECLR 33
#define EVF 1
#define OCLR 0
#define EPF 0
#define B0DELAY 0
#define PSL 200
#define CTRL 0
#define GB 1
#define GBT 100000u
#define DL2 100000
#define WEARLY 0
#define H1LATE 0
#define NPF 0
#define G1 0
#define EK 1
#define INFL 2
#define THR0 20
#define POLLN 8
#define POLLS0 100
#define POLLS1 400
#define RDELAY 3
constexpr int kJW[7] = {(JW >> 48) & 255, (JW >> 40) & 255, (JW >> 32) & 255, (JW >> 24) & 255, (JW >> 16) & 255, (JW >> 8) & 255, JW & 255};
constexpr int kNEnt = 40;
struct Sched {
  uint16_t e[kNEnt];
  uint64_t kt, vt;
  int wslot[7], went[7], ea;
  bool ok;
};
constexpr Sched make_sched() {
  Sched S{};
  int kind[kNEnt] = {}, idx[kNEnt] = {}, n = 0;
  for (int i = 6 - EK; i <= 6; i++) { kind[n] = 3; idx[n++] = i; }
  if (EK < 1) { kind[n] = 0; idx[n++] = 0; }
  for (int i = 0; i < EK; i++) S.kt |= (uint64_t)(5 - EK + i) << (4 * i);
  for (int j = 0; j <= 16; j++) {
    if (j < 14 && j + 1 >= EK) { kind[n] = 0; idx[n++] = j + 1; }
    if (j == 13) { kind[n] = 0; idx[n++] = 15; }
    for (int i = 0; i < 7; i++) if (kJW[i] == j) { kind[n] = 2; idx[n++] = i; }
    if (j < 16) { kind[n] = 1; idx[n++] = j; }
  }
  S.ok = n == kNEnt;
  int fifo[kNEnt + kNSlot] = {}, head = 0, tail = 0, uses[kNSlot] = {}, fulls[kNSlot] = {}, last[kNSlot] = {};
  for (int i = 0; i < kNSlot; i++) { if (i < 5 - EK) fifo[tail++] = i; uses[i] = 1; fulls[i] = 1; last[i] = -100; }
  for (int e = 0; e < kNEnt; e++) {
    if (e == EK) fifo[tail++] = 5;
    if (e == EK + 1) for (int i = 0; i < EK; i++) fifo[tail++] = 5 - EK + i;
    if (head == tail) { S.ok = false; break; }
    const int sl = fifo[head++];
    if (e - last[sl] <= RDELAY) S.ok = false;
    last[sl] = -100;
    S.e[e] = (uint16_t)(sl | (((uses[sl] - 1) & 1) << 3) | (kind[e] << 4) | (idx[e] << 6));
    uses[sl]++;
    if (kind[e] == 2) {
      S.wslot[idx[e]] = sl; S.went[idx[e]] = e;
      if (idx[e] < 3) { fifo[tail++] = sl; last[sl] = e; }
    } else {
      const uint64_t f = (uint64_t)(sl | ((fulls[sl] & 1) << 3)) << (4 * idx[e]);
      if (kind[e] == 0) S.kt |= f; else if (kind[e] == 1) S.vt |= f;
      if (kind[e] == 1 && idx[e] == 14) S.ea = e;
      S.e[e] = (uint16_t)(S.e[e] | ((fulls[sl] & 1) << 10));
      fulls[sl]++;
      fifo[tail++] = sl;
    }
  }
  for (int i = 3; i < 7; i++)
    if (S.wslot[i] == (int)((S.vt >> 56) & 7) || S.wslot[i] == (int)((S.vt >> 60) & 7)) S.ok = false;
  return S;
}
constexpr Sched kS = make_sched();
static_assert(kS.ok && kS.went[6] == kNEnt - 1, "ring schedule");
__constant__ Sched cS = make_sched();
constexpr uint64_t kKT = kS.kt, kVT = kS.vt;
__host__ __device__ constexpr uint32_t slot_of(uint64_t t, int i) { return (uint32_t)(t >> (4 * i)) & 7u; }
__host__ __device__ constexpr uint32_t par_of(uint64_t t, int i) { return (uint32_t)(t >> (4 * i + 3)) & 1u; }
constexpr uint32_t kSlotV14 = slot_of(kVT, 14);
static_assert(slot_of(kVT, 13) != slot_of(kVT, 14) && slot_of(kVT, 13) != slot_of(kVT, 15) && slot_of(kVT, 14) != slot_of(kVT, 15) &&
              slot_of(kKT, 14) != slot_of(kKT, 15), "the end game keeps these tiles at the same time");
constexpr int kEntA = kS.ea;
static_assert(((kS.e[kEntA + 1] >> 4) & 3) == 1 && ((kS.e[kEntA - 1] >> 4) & 3) == 1 &&
              ECLR < kEntA && ECLR >= THR0 && THR0 - 2 > kS.went[2] + RDELAY, "producer phases");
constexpr int kEntR0 = kS.went[0], kEntR1 = kS.went[1], kEntR2 = kS.went[2];
constexpr int kW0 = kS.wslot[0], kW1 = kS.wslot[1], kW2 = kS.wslot[2], kW3 = kS.wslot[3], kW4 = kS.wslot[4], kW5 = kS.wslot[5], kW6 = kS.wslot[6];

__device__ uint4 g_part[kB * kHkv * kPartW];
__device__ unsigned g_epoch[kB];
__device__ unsigned g_prog[2];

__device__ __forceinline__ uint32_t smem_u32(const void* p) { return (uint32_t)__cvta_generic_to_shared(p); }
__device__ __forceinline__ void mbar_init(uint32_t bar, uint32_t cnt) {
  asm volatile("mbarrier.init.shared::cta.b64 [%0], %1;" ::"r"(bar), "r"(cnt) : "memory");
}
__device__ __forceinline__ void mbar_expect_tx(uint32_t bar, uint32_t bytes) {
  asm volatile("mbarrier.arrive.expect_tx.shared::cta.b64 _, [%0], %1;" ::"r"(bar), "r"(bytes) : "memory");
}
__device__ __forceinline__ void mbar_arrive(uint32_t bar) {
  asm volatile("mbarrier.arrive.shared::cta.b64 _, [%0];" ::"r"(bar) : "memory");
}
__device__ __forceinline__ void mbar_arrive_cluster(uint32_t cluster_addr) {
  asm volatile("mbarrier.arrive.relaxed.cluster.shared::cluster.b64 _, [%0];" ::"r"(cluster_addr) : "memory");
}
__device__ __forceinline__ bool mbar_try(uint32_t bar, uint32_t parity) {
  uint32_t ok;
  asm volatile("{\n.reg .pred p;\nmbarrier.try_wait.parity.shared::cta.b64 p, [%1], %2;\nselp.u32 %0, 1, 0, p;\n}\n"
               : "=r"(ok) : "r"(bar), "r"(parity) : "memory");
  return ok != 0;
}
__device__ __forceinline__ bool mbar_test(uint32_t bar, uint32_t parity) {
  uint32_t ok;
  asm volatile("{\n.reg .pred p;\nmbarrier.test_wait.parity.shared::cta.b64 p, [%1], %2;\nselp.u32 %0, 1, 0, p;\n}\n"
               : "=r"(ok) : "r"(bar), "r"(parity) : "memory");
  return ok != 0;
}
__device__ __forceinline__ bool mbar_try_cluster(uint32_t bar, uint32_t parity) {
  uint32_t ok;
  asm volatile("{\n.reg .pred p;\nmbarrier.try_wait.parity.acquire.cluster.shared::cta.b64 p, [%1], %2;\nselp.u32 %0, 1, 0, p;\n}\n"
               : "=r"(ok) : "r"(bar), "r"(parity) : "memory");
  return ok != 0;
}
constexpr long long kSpinLimit = 4000000000ll;
constexpr uint32_t kTryLimit = 1u << 26;
__device__ __forceinline__ void mbar_wait(uint32_t bar, uint32_t parity) {
  uint32_t n = 0;
  while (!mbar_try(bar, parity)) { if (++n > kTryLimit) __trap(); }
}
__device__ __forceinline__ void mbar_wait_cluster(uint32_t bar, uint32_t parity) {
  uint32_t n = 0;
  while (!mbar_try_cluster(bar, parity)) { if (++n > kTryLimit) __trap(); }
}
__device__ __forceinline__ uint32_t mapa(uint32_t addr, uint32_t rank) {
  uint32_t r;
  asm volatile("mapa.shared::cluster.u32 %0, %1, %2;" : "=r"(r) : "r"(addr), "r"(rank));
  return r;
}
__device__ __forceinline__ void tma_3d(uint32_t dst, const CUtensorMap* tm, uint32_t bar, int c0, int c1, int c2) {
  asm volatile("cp.async.bulk.tensor.3d.shared::cluster.global.mbarrier::complete_tx::bytes [%0], [%1, {%3, %4, %5}], [%2];"
               ::"r"(dst), "l"(tm), "r"(bar), "r"(c0), "r"(c1), "r"(c2) : "memory");
}
__device__ __forceinline__ void tma_3d_h(uint32_t dst, const CUtensorMap* tm, uint32_t bar, int c0, int c1, int c2, uint64_t pol) {
  asm volatile("cp.async.bulk.tensor.3d.shared::cluster.global.mbarrier::complete_tx::bytes.L2::cache_hint [%0], [%1, {%3, %4, %5}], [%2], %6;"
               ::"r"(dst), "l"(tm), "r"(bar), "r"(c0), "r"(c1), "r"(c2), "l"(pol) : "memory");
}
__device__ __forceinline__ void tma_4d(uint32_t dst, const CUtensorMap* tm, uint32_t bar, int c0, int c1, int c2, int c3) {
  asm volatile("cp.async.bulk.tensor.4d.shared::cluster.global.mbarrier::complete_tx::bytes [%0], [%1, {%3, %4, %5, %6}], [%2];"
               ::"r"(dst), "l"(tm), "r"(bar), "r"(c0), "r"(c1), "r"(c2), "r"(c3) : "memory");
}
__device__ __forceinline__ void st_b128(uint4* p, uint32_t x, uint32_t y, uint32_t z, uint32_t w) {
  asm volatile("{\n.reg .b128 t;\nmov.b128 t, {%1, %2, %3, %4};\nst.relaxed.gpu.global.b128 [%0], t;\n}\n"
               ::"l"(p), "r"(x), "r"(y), "r"(z), "r"(w) : "memory");
}
__device__ __forceinline__ void ld_b128(uint4& v, const uint4* p) {
  asm volatile("{\n.reg .b128 t;\nld.relaxed.gpu.global.b128 t, [%4];\nmov.b128 {%0, %1, %2, %3}, t;\n}\n"
               : "=r"(v.x), "=r"(v.y), "=r"(v.z), "=r"(v.w) : "l"(p) : "memory");
}
__device__ __forceinline__ bool __syncthreads_and_wg(bool p) {
  uint32_t r;
  asm volatile("{\n.reg .pred a, b;\nsetp.ne.u32 a, %1, 0;\nbar.red.and.pred b, 2, 128, a;\nselp.u32 %0, 1, 0, b;\n}\n"
               : "=r"(r) : "r"((uint32_t)p) : "memory");
  return r != 0;
}
__device__ __forceinline__ void fence_proxy_async() { asm volatile("fence.proxy.async.shared::cta;" ::: "memory"); }
__device__ __forceinline__ void wgmma_fence() { asm volatile("wgmma.fence.sync.aligned;" ::: "memory"); }
__device__ __forceinline__ void wgmma_commit() { asm volatile("wgmma.commit_group.sync.aligned;" ::: "memory"); }
template <int N> __device__ __forceinline__ void wgmma_wait() { asm volatile("wgmma.wait_group.sync.aligned %0;" ::"n"(N) : "memory"); }
__device__ __forceinline__ float ex2(float x) { float y; asm("ex2.approx.ftz.f32 %0, %1;" : "=f"(y) : "f"(x)); return y; }
__device__ __forceinline__ float rcp(float x) { float y; asm("rcp.approx.ftz.f32 %0, %1;" : "=f"(y) : "f"(x)); return y; }
__device__ __forceinline__ uint32_t pack_bf16(float lo, float hi) {
  uint32_t r; asm("cvt.rn.bf16x2.f32 %0, %1, %2;" : "=r"(r) : "f"(hi), "f"(lo)); return r;
}
__device__ __forceinline__ uint64_t make_desc(uint32_t base16, uint32_t off, uint32_t lbo) {
  return ((uint64_t)0x40000040u << 32) | (uint64_t)(base16 + (off >> 4) + ((lbo >> 4) << 16));
}
template <typename T> __device__ __forceinline__ void fence_regs(T& r) { asm volatile("" : "+f"(r)::"memory"); }
template <int OFF> __device__ __forceinline__ void fence_half(float (&a)[64]) {
#pragma unroll
  for (int i = 0; i < 32; i++) fence_regs(a[OFF + i]);
}
template <int N> __device__ __forceinline__ void fence_arr(float (&a)[N]) {
#pragma unroll
  for (int i = 0; i < N; i++) fence_regs(a[i]);
}

__device__ __forceinline__ void wgmma_ss_n64(float (&d)[32], uint64_t da, uint64_t db, int scale_d) {
  asm volatile("{\n.reg .pred p;\nsetp.ne.b32 p, %34, 0;\n"
    "wgmma.mma_async.sync.aligned.m64n64k16.f32.bf16.bf16 {%0, %1, %2, %3, %4, %5, %6, %7, %8, %9, %10, %11, %12, %13, %14, %15, %16, %17, %18, %19, %20, %21, %22, %23, %24, %25, %26, %27, %28, %29, %30, %31}, %32, %33, p, 1, 1, 0, 0;\n}\n"
    : "+f"(d[0]), "+f"(d[1]), "+f"(d[2]), "+f"(d[3]), "+f"(d[4]), "+f"(d[5]), "+f"(d[6]), "+f"(d[7]), "+f"(d[8]), "+f"(d[9]), "+f"(d[10]), "+f"(d[11]), "+f"(d[12]), "+f"(d[13]), "+f"(d[14]), "+f"(d[15]), "+f"(d[16]), "+f"(d[17]), "+f"(d[18]), "+f"(d[19]), "+f"(d[20]), "+f"(d[21]), "+f"(d[22]), "+f"(d[23]), "+f"(d[24]), "+f"(d[25]), "+f"(d[26]), "+f"(d[27]), "+f"(d[28]), "+f"(d[29]), "+f"(d[30]), "+f"(d[31])
    : "l"(da), "l"(db), "r"(scale_d));
}
__device__ __forceinline__ void wgmma_rs_n128_tb(float (&d)[64], uint32_t a0, uint32_t a1, uint32_t a2, uint32_t a3, uint64_t db) {
  asm volatile(
    "wgmma.mma_async.sync.aligned.m64n128k16.f32.bf16.bf16 {%0, %1, %2, %3, %4, %5, %6, %7, %8, %9, %10, %11, %12, %13, %14, %15, %16, %17, %18, %19, %20, %21, %22, %23, %24, %25, %26, %27, %28, %29, %30, %31, %32, %33, %34, %35, %36, %37, %38, %39, %40, %41, %42, %43, %44, %45, %46, %47, %48, %49, %50, %51, %52, %53, %54, %55, %56, %57, %58, %59, %60, %61, %62, %63}, {%64, %65, %66, %67}, %68, 1, 1, 1, 1;\n"
    : "+f"(d[0]), "+f"(d[1]), "+f"(d[2]), "+f"(d[3]), "+f"(d[4]), "+f"(d[5]), "+f"(d[6]), "+f"(d[7]), "+f"(d[8]), "+f"(d[9]), "+f"(d[10]), "+f"(d[11]), "+f"(d[12]), "+f"(d[13]), "+f"(d[14]), "+f"(d[15]), "+f"(d[16]), "+f"(d[17]), "+f"(d[18]), "+f"(d[19]), "+f"(d[20]), "+f"(d[21]), "+f"(d[22]), "+f"(d[23]), "+f"(d[24]), "+f"(d[25]), "+f"(d[26]), "+f"(d[27]), "+f"(d[28]), "+f"(d[29]), "+f"(d[30]), "+f"(d[31]), "+f"(d[32]), "+f"(d[33]), "+f"(d[34]), "+f"(d[35]), "+f"(d[36]), "+f"(d[37]), "+f"(d[38]), "+f"(d[39]), "+f"(d[40]), "+f"(d[41]), "+f"(d[42]), "+f"(d[43]), "+f"(d[44]), "+f"(d[45]), "+f"(d[46]), "+f"(d[47]), "+f"(d[48]), "+f"(d[49]), "+f"(d[50]), "+f"(d[51]), "+f"(d[52]), "+f"(d[53]), "+f"(d[54]), "+f"(d[55]), "+f"(d[56]), "+f"(d[57]), "+f"(d[58]), "+f"(d[59]), "+f"(d[60]), "+f"(d[61]), "+f"(d[62]), "+f"(d[63])
    : "r"(a0), "r"(a1), "r"(a2), "r"(a3), "l"(db));
}
__device__ __forceinline__ void wgmma_rs_n32(float (&d)[16], uint32_t a0, uint32_t a1, uint32_t a2, uint32_t a3, uint64_t db, int scale_d) {
  asm volatile("{\n.reg .pred p;\nsetp.ne.b32 p, %21, 0;\n"
    "wgmma.mma_async.sync.aligned.m64n32k16.f32.bf16.bf16 {%0, %1, %2, %3, %4, %5, %6, %7, %8, %9, %10, %11, %12, %13, %14, %15}, {%16, %17, %18, %19}, %20, p, 1, 1, 0;\n}\n"
    : "+f"(d[0]), "+f"(d[1]), "+f"(d[2]), "+f"(d[3]), "+f"(d[4]), "+f"(d[5]), "+f"(d[6]), "+f"(d[7]), "+f"(d[8]), "+f"(d[9]), "+f"(d[10]), "+f"(d[11]), "+f"(d[12]), "+f"(d[13]), "+f"(d[14]), "+f"(d[15])
    : "r"(a0), "r"(a1), "r"(a2), "r"(a3), "l"(db), "r"(scale_d));
}
__device__ __forceinline__ void wgmma_ss_n32_ta(float (&d)[16], uint64_t da, uint64_t db, int scale_d) {
  asm volatile("{\n.reg .pred p;\nsetp.ne.b32 p, %18, 0;\n"
    "wgmma.mma_async.sync.aligned.m64n32k16.f32.bf16.bf16 {%0, %1, %2, %3, %4, %5, %6, %7, %8, %9, %10, %11, %12, %13, %14, %15}, %16, %17, p, 1, 1, 1, 0;\n}\n"
    : "+f"(d[0]), "+f"(d[1]), "+f"(d[2]), "+f"(d[3]), "+f"(d[4]), "+f"(d[5]), "+f"(d[6]), "+f"(d[7]), "+f"(d[8]), "+f"(d[9]), "+f"(d[10]), "+f"(d[11]), "+f"(d[12]), "+f"(d[13]), "+f"(d[14]), "+f"(d[15])
    : "l"(da), "l"(db), "r"(scale_d));
}

template <int OFF>
__device__ __forceinline__ void wgmma_rs_n64_tb(float (&d)[64], uint32_t a0, uint32_t a1, uint32_t a2, uint32_t a3, uint64_t db) {
  asm volatile(
    "wgmma.mma_async.sync.aligned.m64n64k16.f32.bf16.bf16 {%0, %1, %2, %3, %4, %5, %6, %7, %8, %9, %10, %11, %12, %13, %14, %15, %16, %17, %18, %19, %20, %21, %22, %23, %24, %25, %26, %27, %28, %29, %30, %31}, {%32, %33, %34, %35}, %36, 1, 1, 1, 1;\n"
    : "+f"(d[OFF + 0]), "+f"(d[OFF + 1]), "+f"(d[OFF + 2]), "+f"(d[OFF + 3]), "+f"(d[OFF + 4]), "+f"(d[OFF + 5]), "+f"(d[OFF + 6]), "+f"(d[OFF + 7]), "+f"(d[OFF + 8]), "+f"(d[OFF + 9]), "+f"(d[OFF + 10]), "+f"(d[OFF + 11]), "+f"(d[OFF + 12]), "+f"(d[OFF + 13]), "+f"(d[OFF + 14]), "+f"(d[OFF + 15]), "+f"(d[OFF + 16]), "+f"(d[OFF + 17]), "+f"(d[OFF + 18]), "+f"(d[OFF + 19]), "+f"(d[OFF + 20]), "+f"(d[OFF + 21]), "+f"(d[OFF + 22]), "+f"(d[OFF + 23]), "+f"(d[OFF + 24]), "+f"(d[OFF + 25]), "+f"(d[OFF + 26]), "+f"(d[OFF + 27]), "+f"(d[OFF + 28]), "+f"(d[OFF + 29]), "+f"(d[OFF + 30]), "+f"(d[OFF + 31])
    : "r"(a0), "r"(a1), "r"(a2), "r"(a3), "l"(db));
}

#define TS(i) do {} while (0)

__global__ void __cluster_dims__(2, 1, 1) __launch_bounds__(kThreads, 1)
fused_attn_kernel(const __grid_constant__ CUtensorMap tmK, const __grid_constant__ CUtensorMap tmV,
                  const __grid_constant__ CUtensorMap tmX, const __grid_constant__ CUtensorMap tmWq,
                  const __grid_constant__ CUtensorMap tmWo, const __grid_constant__ CUtensorMap tmV2,
                  __nv_bfloat16* __restrict__ out) {
  extern __shared__ uint8_t smem_raw[];
  const uint32_t sbase = (smem_u32(smem_raw) + 1023u) & ~1023u;
  const uint32_t s16 = (sbase & 0x3FFFFu) >> 4, q16 = s16 + (kQOff >> 4);
  const int tid = threadIdx.x, warp = tid >> 5, lane = tid & 31;
  const int cta = blockIdx.x;
  const int b = cta >> 4, hkv = (cta >> 1) & 7, s = cta & 1;
  const int h = hkv * 2 + s;
  const uint32_t misc = sbase + kMiscOff;
  const uint32_t bar_full = misc, bar_empty = misc + 48, bar_w0 = misc + 96, bar_q = misc + 104, bar_qfree = misc + 112;
  const uint32_t tagw = misc + 120;
  const uint32_t bar_s = misc + 128, bar_wo = misc + 160, bar_o = misc + 224;
  const uint32_t bar_m = misc + 288, bar_lz = misc + 296, bar_m2 = misc + 304, bar_b1 = misc + 312;
  const uint32_t stats = misc + 320, bar_x = misc + 832, bar_c = misc + 960, progw = misc + 968;
  const uint32_t qbase = sbase + kQOff;
  const int row0 = (b * kHkv + hkv) * kSk + (kSk - kW) + s * (kW / 2);

  if (tid == 128) {
    for (int i = 0; i < kNSlot; i++) mbar_init(bar_full + 8 * i, 1);
    mbar_init(bar_w0, 1);
    fence_proxy_async();
    mbar_expect_tx(bar_full + 8 * 5, 7 * 4096);
    tma_3d(sbase + 5 * kSlot, &tmX, bar_full + 8 * 5, 0, b * kSq, 0);
    mbar_expect_tx(bar_w0, kSlot);
    tma_3d(qbase, &tmWq, bar_w0, 0, 0, h * 4);
#pragma unroll 1
    for (int i = 0; i < 5; i++) {
      mbar_expect_tx(bar_full + 8 * i, kSlot);
      if (i < 5 - EK) tma_3d(sbase + i * kSlot, &tmWq, bar_full + 8 * i, 0, (i + 1) * 64, h * 4);
      else tma_3d_h(sbase + i * kSlot, &tmK, bar_full + 8 * i, 0, row0 + (i - 5 + EK) * 64, 0, 0x12F0000000000000ull);
    }
  } else if (tid == 160) {
    for (int i = 0; i < kNSlot; i++) mbar_init(bar_empty + 8 * i, 4);
    for (int i = 0; i < 7; i++) mbar_init(bar_wo + 8 * i, 1);
    mbar_init(bar_q, 1); mbar_init(bar_qfree, 4); mbar_init(bar_m, 5); mbar_init(bar_c, 1); mbar_init(bar_lz, 4);
    mbar_init(bar_m2, 4); mbar_init(bar_b1, 1);
    asm volatile("st.shared.v2.u32 [%0], {%1, %1};" ::"r"(progw), "r"(0u) : "memory");
    for (int i = 0; i < 4; i++) mbar_init(bar_s + 8 * i, 1);
    for (int i = 0; i < 8; i++) mbar_init(bar_o + 8 * i, 1);
    for (int i = 0; i < 16; i++) mbar_init(bar_x + 8 * i, 1);
    mbar_expect_tx(bar_q, 16384);
    for (int i = 0; i < 4; i++) mbar_expect_tx(bar_s + 8 * i, 128);
    for (int i = 0; i < 8; i++) mbar_expect_tx(bar_o + 8 * i, 2048);
    for (int i = 0; i < 16; i++) mbar_expect_tx(bar_x + 8 * i, i < 12 ? 1024 : 512);
    asm volatile("fence.mbarrier_init.release.cluster;" ::: "memory");
    fence_proxy_async();
  } else if (tid >= 192 && tid < 196) {
    asm volatile("prefetch.tensormap [%0];" ::"l"(tid == 192 ? &tmK : tid == 193 ? &tmV : tid == 194 ? &tmWo : &tmV2) : "memory");
  }
  __syncthreads();
  asm volatile("barrier.cluster.arrive.relaxed.aligned;" ::: "memory");

  const int wg = warp >> 2, w = warp & 3, g = lane >> 2, t = lane & 3;
  const uint32_t peer = (uint32_t)(s ^ 1);
  unsigned tag;
  uint4* part = g_part + (size_t)(b * kHkv + hkv) * kPartW + s * 7 * 128 + (tid & 127);

  const uint32_t lz = sbase + (uint32_t)kSlotV14 * kSlot + (uint32_t)(tid & 127) * 16u;
  auto send_word = [&](const float* d, int L, int i) {
    const uint32_t dst = mapa(lz + (uint32_t)L * 4096u + (uint32_t)i * 2048u, peer), rb = mapa(bar_x + 8u * (uint32_t)(4 * L + w), peer);
    asm volatile("st.async.weak.shared::cluster.mbarrier::complete_tx::bytes.v4.b32 [%0], {%1, %2, %3, %4}, [%5];"
                 ::"r"(dst), "r"(pack_bf16(d[0], d[1])), "r"(pack_bf16(d[2], d[3])), "r"(pack_bf16(d[4], d[5])), "r"(pack_bf16(d[6], d[7])), "r"(rb) : "memory");
  };
  auto finish_word = [&](const float* d, int L, int i, int word) {
    uint32_t x0, x1, x2, x3;
    asm volatile("ld.shared.v4.u32 {%0, %1, %2, %3}, [%4];" : "=r"(x0), "=r"(x1), "=r"(x2), "=r"(x3)
                 : "r"(lz + (uint32_t)L * 4096u + (uint32_t)i * 2048u) : "memory");
    const uint32_t off = tag << 16;
    const uint32_t v0 = ((__float_as_uint(d[0] + __uint_as_float(x0 << 16)) - off + 0x10000u) & 0xfffe0000u) + off;
    x0 = __byte_perm(v0, pack_bf16(0.f, d[1] + __uint_as_float(x0 & 0xffff0000u)), 0x7632);
    x1 = pack_bf16(d[2] + __uint_as_float(x1 << 16), d[3] + __uint_as_float(x1 & 0xffff0000u));
    x2 = pack_bf16(d[4] + __uint_as_float(x2 << 16), d[5] + __uint_as_float(x2 & 0xffff0000u));
    x3 = pack_bf16(d[6] + __uint_as_float(x3 << 16), d[7] + __uint_as_float(x3 & 0xffff0000u));
    st_b128(part + word * 128, x0, x1, x2, x3);
  };
  auto send_tile = [&](const float (&d)[16], int L) { send_word(d, L, 0); send_word(d + 8, L, 1); };
  auto finish_tile = [&](const float (&d)[16], int L) {
    mbar_wait_cluster(bar_x + 8u * (uint32_t)(4 * L + w), 0);
    finish_word(d, L, 0, s + 2 * L); finish_word(d + 8, L, 1, s + 2 * L + 1);
  };
  auto o_desc = [&](int kk) {
    return make_desc(q16, (uint32_t)(2 + ((kk >> 2) & 1)) * 8192u + (uint32_t)(kk >> 3) * 4096u + (uint32_t)(kk & 3) * 32u, 16);
  };
  auto ldsm_tile = [&](uint32_t (&A)[16][4], int sl, int ins, int hm) {
    mbar_wait(bar_wo + 8 * ins, 0);
    const uint32_t mi = (uint32_t)lane >> 3;
    const uint32_t k = 8u * (mi >> 1) + ((uint32_t)lane & 7u);
    const uint32_t addr = sbase + (uint32_t)sl * kSlot + k * 128u + ((((uint32_t)(2 * w) + (mi & 1u)) ^ (k & 7u)) << 4);
#pragma unroll
    for (int kk = 0; kk < 16; kk++)
      if ((hm >> ((kk >> 2) & 1)) & 1)
        asm volatile("ldmatrix.sync.aligned.m8n8.x4.trans.shared.b16 {%0, %1, %2, %3}, [%4];"
                     : "=r"(A[kk][0]), "=r"(A[kk][1]), "=r"(A[kk][2]), "=r"(A[kk][3]) : "r"(addr + kk * 2048) : "memory");
  };
  auto oproj = [&](float (&d)[16], const uint32_t (&A)[16][4], int hf) {
#pragma unroll
    for (int kk = 0; kk < 16; kk++)
      if (((kk >> 2) & 1) == hf || hf == 2) wgmma_rs_n32(d, A[kk][0], A[kk][1], A[kk][2], A[kk][3], o_desc(kk), kk != 0);
    wgmma_commit();
  };
  auto oproj_s = [&](float (&d)[16], int sl, int hf) {
#pragma unroll
    for (int kk = 0; kk < 16; kk++)
      if (((kk >> 2) & 1) == hf) wgmma_ss_n32_ta(d, make_desc(s16 + (uint32_t)sl * (kSlot >> 4), kk * 2048, 8192), o_desc(kk), kk != 0);
    wgmma_commit();
  };
  auto zero16 = [&](float (&d)[16]) {
#pragma unroll
    for (int i = 0; i < 16; i++) d[i] = 0.f;
    fence_arr(d);
  };

  if (wg == 0) {
    {
      float a[4][16];
#pragma unroll
      for (int mt = 0; mt < 4; mt++) {
#pragma unroll
        for (int i = 0; i < 16; i++) a[mt][i] = 0.f;
        fence_arr(a[mt]);
      }
      mbar_wait(bar_full + 8 * 5, 0);
#pragma unroll 1
      for (int kt = 0; kt < 7; kt++) {
        const uint32_t sl = kt >= 6 - EK ? (uint32_t)(kt - 6 + EK) : (uint32_t)kt - 1u;
        const uint32_t wb = kt == 0 ? q16 : s16 + sl * (kSlot >> 4);
        const uint32_t xb = s16 + ((5 * kSlot) >> 4) + (uint32_t)kt * 256u;
        mbar_wait(kt == 0 ? bar_w0 : bar_full + 8 * sl, kt >= 6 - EK ? 1 : 0);
        wgmma_fence();
#pragma unroll
        for (int kk = 0; kk < 4; kk++) {
#pragma unroll
          for (int mt = 0; mt < 4; mt++)
            wgmma_ss_n32_ta(a[mt], make_desc(wb, mt * 8192 + kk * 2048, 8192), make_desc(xb, kk * 32, 16), 1);
        }
        wgmma_commit();
        wgmma_wait<1>();
        if (kt == 1) {
          asm volatile("barrier.cluster.wait.acquire.aligned;" ::: "memory");
          if (lane == 0) mbar_arrive_cluster(mapa(bar_qfree, peer));
        } else if (kt > 1 && lane == 0) {
          mbar_arrive(bar_empty + 8 * (kt - 1 >= 6 - EK ? kt - 7 + EK : kt - 2));
        }
      }
      wgmma_wait<0>();
#pragma unroll
      for (int mt = 0; mt < 4; mt++) fence_arr(a[mt]);
      if (lane == 0) { mbar_arrive(bar_empty + 8 * EK); mbar_arrive(bar_empty + 8 * 5); }
      asm volatile("bar.sync 2, 128;" ::: "memory");
      const uint32_t mi = (uint32_t)lane >> 3;
      const uint32_t u = (uint32_t)(2 * w) + (mi & 1u);
#pragma unroll
      for (int mt = 0; mt < 4; mt++) {
#pragma unroll
        for (int j = 0; j < 4; j += 2) {
          const uint32_t r = (uint32_t)(32 * s + 8 * j) + 8u * (mi >> 1) + ((uint32_t)lane & 7u);
          const uint32_t addr = qbase + mt * 8192 + r * 128u + ((u ^ (r & 7u)) << 4);
          const uint32_t y0 = pack_bf16(a[mt][4 * j], a[mt][4 * j + 1]), y1 = pack_bf16(a[mt][4 * j + 2], a[mt][4 * j + 3]);
          const uint32_t y2 = pack_bf16(a[mt][4 * j + 4], a[mt][4 * j + 5]), y3 = pack_bf16(a[mt][4 * j + 6], a[mt][4 * j + 7]);
          asm volatile("stmatrix.sync.aligned.m8n8.x4.trans.shared.b16 [%0], {%1, %2, %3, %4};"
                       ::"r"(addr), "r"(y0), "r"(y1), "r"(y2), "r"(y3) : "memory");
        }
      }
      fence_proxy_async();
      asm volatile("bar.sync 2, 128;" ::: "memory");
      if (tid == 0) {
        mbar_wait_cluster(bar_qfree, 0);
        const uint32_t dst = mapa(qbase + (uint32_t)s * 4096u, peer), rb = mapa(bar_q, peer);
#pragma unroll
        for (int mt = 0; mt < 4; mt++)
          asm volatile("cp.async.bulk.shared::cluster.shared::cta.mbarrier::complete_tx::bytes [%0], [%1], 4096, [%2];"
                       ::"r"(dst + mt * 8192), "r"(qbase + (uint32_t)s * 4096u + mt * 8192), "r"(rb) : "memory");
      }
      __syncwarp();
    }

    const float c = 0.0625f * 1.4426950408889634f;
    float oA[64], oB[64];
    float sc[32];
    uint32_t p[16];
#pragma unroll
    for (int i = 0; i < 64; i++) { oA[i] = 0.f; oB[i] = 0.f; }
#pragma unroll
    for (int i = 0; i < 32; i++) sc[i] = 0.f;
#pragma unroll
    for (int i = 0; i < 16; i++) p[i] = 0u;
    fence_arr(oA); fence_arr(oB); fence_arr(sc);
    float m0 = -INFINITY, m1 = -INFINITY, l0 = 0.f, l1 = 0.f;
    const uint32_t offA = (uint32_t)(s ^ 1) * 1024u, offB = (uint32_t)s * 1024u;
    auto pv_half = [&](float (&o)[64], const uint32_t (&pp)[16], uint32_t vb) {
#pragma unroll
      for (int kk = 0; kk < 4; kk++)
        wgmma_rs_n128_tb(o, pp[4 * kk], pp[4 * kk + 1], pp[4 * kk + 2], pp[4 * kk + 3], make_desc(vb, kk * 2048, 8192));
    };
    auto pv_issue = [&](uint32_t vb) {
      wgmma_fence();
      pv_half(oA, p, vb + offA);
      wgmma_commit();
      pv_half(oB, p, vb + offB);
      wgmma_commit();
    };
    auto qk_issue = [&](float (&d)[32], uint32_t kb) {
      wgmma_fence();
#pragma unroll
      for (int kk = 0; kk < 16; kk++) {
        const uint32_t off = (uint32_t)(kk >> 2) * 8192u + (uint32_t)(kk & 3) * 32u;
        wgmma_ss_n64(d, make_desc(q16, off, 16), make_desc(kb, off, 16), kk != 0);
      }
      wgmma_commit();
    };
    auto softmax = [&](float (&d)[32], float& f0, float& f1) {
      float mx0 = d[0], mx1 = d[2];
#pragma unroll
      for (int j = 0; j < 8; j++) {
        mx0 = fmaxf(mx0, fmaxf(d[4 * j], d[4 * j + 1]));
        mx1 = fmaxf(mx1, fmaxf(d[4 * j + 2], d[4 * j + 3]));
      }
      mx0 = fmaxf(mx0, __shfl_xor_sync(0xffffffffu, mx0, 1)); mx0 = fmaxf(mx0, __shfl_xor_sync(0xffffffffu, mx0, 2));
      mx1 = fmaxf(mx1, __shfl_xor_sync(0xffffffffu, mx1, 1)); mx1 = fmaxf(mx1, __shfl_xor_sync(0xffffffffu, mx1, 2));
      const float n0 = fmaxf(m0, mx0), n1 = fmaxf(m1, mx1);
      f0 = ex2((m0 - n0) * c); f1 = ex2((m1 - n1) * c);
      m0 = n0; m1 = n1;
      const float mc0 = m0 * c, mc1 = m1 * c;
      float s0 = 0.f, s1 = 0.f;
#pragma unroll
      for (int j = 0; j < 8; j++) {
        d[4 * j] = ex2(fmaf(d[4 * j], c, -mc0)); d[4 * j + 1] = ex2(fmaf(d[4 * j + 1], c, -mc0));
        d[4 * j + 2] = ex2(fmaf(d[4 * j + 2], c, -mc1)); d[4 * j + 3] = ex2(fmaf(d[4 * j + 3], c, -mc1));
        s0 += d[4 * j] + d[4 * j + 1]; s1 += d[4 * j + 2] + d[4 * j + 3];
      }
      l0 = fmaf(l0, f0, s0); l1 = fmaf(l1, f1, s1);
    };
    auto scale = [&](float (&o)[64], float f0, float f1) {
#pragma unroll
      for (int j = 0; j < 16; j++) { o[4 * j] *= f0; o[4 * j + 1] *= f0; o[4 * j + 2] *= f1; o[4 * j + 3] *= f1; }
    };

    if (tid == 0) TS(26);
    mbar_wait_cluster(bar_q, 0);
    if (tid == 0) TS(34);
#pragma unroll 1
    for (int it = 0; it < 14; it++) {
      const uint32_t ke = (uint32_t)(kKT >> (4 * it)), ks = ke & 7u;
      mbar_wait(bar_full + 8 * ks, (ke >> 3) & 1u);
      if (tid == 0) TS(48 + it);
      qk_issue(sc, s16 + ks * (kSlot >> 4));
      uint32_t vs = ks;
      bool held = it > 0;
      if (it > 0) {
        const uint32_t ve = (uint32_t)(kVT >> (4 * it - 4)), phase = (ve >> 3) & 1u;
        vs = ve & 7u;
        if (!__all_sync(0xffffffffu, mbar_test(bar_full + 8 * vs, phase))) {
          wgmma_wait<0>();
          if (lane == 0) mbar_arrive(bar_empty + 8 * ks);
          held = false;
          mbar_wait(bar_full + 8 * vs, phase);
        }
      }
      pv_issue(s16 + vs * (kSlot >> 4));
      wgmma_wait<2>();
      fence_arr(sc);
      if (lane == 0 && held) mbar_arrive(bar_empty + 8 * ks);
      float f0, f1;
      softmax(sc, f0, f1);
      fence_arr(sc);
      mbar_wait(bar_w0, 0);
      wgmma_wait<0>();
      fence_arr(oA); fence_arr(oB);
      if (lane == 0) mbar_arrive(bar_empty + 8 * vs);
      if (__any_sync(0xffffffffu, (f0 != 1.f) || (f1 != 1.f))) { scale(oA, f0, f1); scale(oB, f0, f1); }
#pragma unroll
      for (int j = 0; j < 8; j++) {
        p[2 * j] = pack_bf16(sc[4 * j], sc[4 * j + 1]);
        p[2 * j + 1] = pack_bf16(sc[4 * j + 2], sc[4 * j + 3]);
      }
    }
    uint32_t pb[16], pc[16];
    float F0, F1;
    {
      constexpr uint32_t k14 = slot_of(kKT, 14), k15 = slot_of(kKT, 15);
      float sb[32];
#pragma unroll
      for (int i = 0; i < 32; i++) sb[i] = 0.f;
      fence_arr(sb);
      if (tid == 0) TS(2);
      mbar_wait(bar_full + 8 * k14, par_of(kKT, 14));
      if (tid == 0) TS(1);
      qk_issue(sc, s16 + k14 * (kSlot >> 4));
      bool held = true;
      if (!__all_sync(0xffffffffu, mbar_test(bar_full + 8 * k15, par_of(kKT, 15)))) {
        wgmma_wait<0>();
        if (lane == 0) mbar_arrive(bar_empty + 8 * k14);
        held = false;
        mbar_wait(bar_full + 8 * k15, par_of(kKT, 15));
      }
      if (tid == 0) TS(27);
      qk_issue(sb, s16 + k15 * (kSlot >> 4));
      wgmma_wait<1>();
      fence_arr(sc);
      if (lane == 0 && held) mbar_arrive(bar_empty + 8 * k14);
      float fa0, fa1, fb0, fb1;
      softmax(sc, fa0, fa1);
      fence_arr(sc);
      mbar_wait(bar_w0, 0);
      wgmma_wait<0>();
      fence_arr(sb);
      if (lane == 0) mbar_arrive(bar_empty + 8 * k15);
      softmax(sb, fb0, fb1);
      l0 += __shfl_xor_sync(0xffffffffu, l0, 1); l0 += __shfl_xor_sync(0xffffffffu, l0, 2);
      l1 += __shfl_xor_sync(0xffffffffu, l1, 1); l1 += __shfl_xor_sync(0xffffffffu, l1, 2);
      const uint32_t sp = mapa(stats + (uint32_t)(16 * w + g) * 8u, peer), rb = mapa(bar_s + 8 * w, peer);
      if (t == 0) {
        asm volatile("st.async.weak.shared::cluster.mbarrier::complete_tx::bytes.v2.f32 [%0], {%1, %2}, [%3];" ::"r"(sp), "f"(m0), "f"(l0), "r"(rb) : "memory");
        asm volatile("st.async.weak.shared::cluster.mbarrier::complete_tx::bytes.v2.f32 [%0], {%1, %2}, [%3];" ::"r"(sp + 64u), "f"(m1), "f"(l1), "r"(rb) : "memory");
      }
      __syncwarp();
      if (tid == 0) TS(7);
#pragma unroll
      for (int j = 0; j < 8; j++) {
        pb[2 * j] = pack_bf16(sc[4 * j] * fb0, sc[4 * j + 1] * fb0);
        pb[2 * j + 1] = pack_bf16(sc[4 * j + 2] * fb1, sc[4 * j + 3] * fb1);
        pc[2 * j] = pack_bf16(sb[4 * j], sb[4 * j + 1]);
        pc[2 * j + 1] = pack_bf16(sb[4 * j + 2], sb[4 * j + 3]);
      }
      F0 = fa0 * fb0; F1 = fa1 * fb1;
    }
    constexpr uint32_t sv13 = slot_of(kVT, 13), sv0 = slot_of(kVT, 14), sv1 = slot_of(kVT, 15);
    using C0 = std::integral_constant<int, 0>;
    using C1 = std::integral_constant<int, 1>;
    auto pv_blk = [&](float (&o)[64], auto hc, uint32_t off) {
      constexpr int H = decltype(hc)::value;
      const uint32_t vv = s16 + (H ? sv1 : sv0) * (kSlot >> 4);
#pragma unroll
      for (int kk = 0; kk < 4; kk++)
        wgmma_rs_n64_tb<32 * H>(o, pb[4 * kk], pb[4 * kk + 1], pb[4 * kk + 2], pb[4 * kk + 3], make_desc(vv, off + kk * 2048, 16384));
#pragma unroll
      for (int kk = 0; kk < 4; kk++)
        wgmma_rs_n64_tb<32 * H>(o, pc[4 * kk], pc[4 * kk + 1], pc[4 * kk + 2], pc[4 * kk + 3], make_desc(vv, off + 8192 + kk * 2048, 16384));
      wgmma_commit();
    };
    if (tid == 0) TS(8);
    mbar_wait(bar_full + 8 * sv13, par_of(kVT, 13));
    if (tid == 0) TS(23);
    pv_issue(s16 + sv13 * (kSlot >> 4));
    wgmma_wait<1>();
    fence_arr(oA);
    scale(oA, F0, F1);
    fence_arr(oA);
    bool held13 = true;
    if (!__all_sync(0xffffffffu, mbar_test(bar_full + 8 * sv0, par_of(kVT, 14)))) {
      wgmma_wait<0>();
      if (lane == 0) mbar_arrive(bar_empty + 8 * sv13);
      held13 = false;
    }
    float r0, r1, u0, u1;
    {
      mbar_wait_cluster(bar_s + 8 * w, 0);
      float pm0, pl0, pm1, pl1;
      asm volatile("ld.shared.v2.f32 {%0, %1}, [%2];" : "=f"(pm0), "=f"(pl0) : "r"(stats + (uint32_t)(16 * w + g) * 8u) : "memory");
      asm volatile("ld.shared.v2.f32 {%0, %1}, [%2];" : "=f"(pm1), "=f"(pl1) : "r"(stats + (uint32_t)(16 * w + g + 8) * 8u) : "memory");
      const float M0 = fmaxf(m0, pm0), M1 = fmaxf(m1, pm1);
      const float e0 = ex2((m0 - M0) * c), e1 = ex2((m1 - M1) * c);
      const float g0 = ex2((pm0 - M0) * c), g1 = ex2((pm1 - M1) * c);
      const float i0 = rcp(l0 * e0 + pl0 * g0), i1 = rcp(l1 * e1 + pl1 * g1);
      r0 = e0 * i0; r1 = e1 * i1; u0 = g0 * i0; u1 = g1 * i1;
      fence_regs(r0); fence_regs(r1); fence_regs(u0); fence_regs(u1);
    }
    asm volatile("ld.shared.u32 %0, [%1];" : "=r"(tag) : "r"(tagw) : "memory");
    mbar_wait(bar_full + 8 * sv0, par_of(kVT, 14));
    if (tid == 0) TS(28);
    wgmma_fence();
    pv_blk(oA, C0{}, 0);
    wgmma_wait<1>();
    fence_arr(oB);
    if (lane == 0 && held13) mbar_arrive(bar_empty + 8 * sv13);
    scale(oB, F0, F1);
    fence_arr(oB);
    wgmma_fence();
    pv_blk(oB, C0{}, 16384);
    const uint32_t land = qbase + (uint32_t)w * 2048u + (uint32_t)lane * 16u;
    auto send_o = [&](auto hc) {
      constexpr int H = decltype(hc)::value;
      fence_half<32 * H>(oA);
      const uint32_t dst = mapa(land + H * 8192, peer), rb = mapa(bar_o + 8 * (4 * H + w), peer);
#pragma unroll
      for (int i = 0; i < 4; i++) {
        const float* o = oA + 32 * H + 8 * i;
        asm volatile("st.async.weak.shared::cluster.mbarrier::complete_tx::bytes.v4.b32 [%0], {%1, %2, %3, %4}, [%5];"
                     ::"r"(dst + i * 512), "r"(pack_bf16(o[0], o[1])), "r"(pack_bf16(o[2], o[3])), "r"(pack_bf16(o[4], o[5])),
                       "r"(pack_bf16(o[6], o[7])), "r"(rb) : "memory");
      }
    };
    auto merge = [&](auto hc) {
      constexpr int H = decltype(hc)::value;
      fence_half<32 * H>(oB);
#pragma unroll
      for (int j = 0; j < 8; j++) {
        oB[32 * H + 4 * j] *= r0; oB[32 * H + 4 * j + 1] *= r0; oB[32 * H + 4 * j + 2] *= r1; oB[32 * H + 4 * j + 3] *= r1;
      }
      fence_half<32 * H>(oB);
      const uint32_t mi = (uint32_t)lane >> 3;
      const uint32_t r = (uint32_t)(16 * w) + 8u * (mi & 1u) + ((uint32_t)lane & 7u);
      mbar_wait_cluster(bar_o + 8 * (4 * H + w), 0);
      if (tid == 0) TS(H ? 18 : 9);
      uint32_t x[4][4];
#pragma unroll
      for (int i = 0; i < 4; i++)
        asm volatile("ld.shared.v4.u32 {%0, %1, %2, %3}, [%4];" : "=r"(x[i][0]), "=r"(x[i][1]), "=r"(x[i][2]), "=r"(x[i][3])
                     : "r"(land + H * 8192 + i * 512) : "memory");
#pragma unroll
      for (int i = 0; i < 4; i++) {
#pragma unroll
        for (int e = 0; e < 4; e++) {
          const float uu = (e & 1) ? u1 : u0;
          x[i][e] = pack_bf16(fmaf(__uint_as_float(x[i][e] << 16), uu, oB[32 * H + 8 * i + 2 * e]),
                              fmaf(__uint_as_float(x[i][e] & 0xffff0000u), uu, oB[32 * H + 8 * i + 2 * e + 1]));
        }
        const uint32_t u = (uint32_t)(2 * i) + (mi >> 1);
        const uint32_t addr = qbase + (uint32_t)(2 + H) * 8192u + r * 128u + ((u ^ (r & 7u)) << 4);
        asm volatile("stmatrix.sync.aligned.m8n8.x4.shared.b16 [%0], {%1, %2, %3, %4};"
                     ::"r"(addr), "r"(x[i][0]), "r"(x[i][1]), "r"(x[i][2]), "r"(x[i][3]) : "memory");
      }
      fence_proxy_async();
      __syncwarp();
      if (lane == 0) mbar_arrive(H ? bar_m2 : bar_m);
    };
    float d3[16], d4[16], d5[16];
    uint32_t B0[16][4], B1[16][4], B2[16][4];
    auto first_half = [&]() {
      zero16(d3); zero16(d4);
      mbar_wait(bar_wo + 8 * 3, 0);
      mbar_wait(bar_wo + 8 * 4, 0);
      mbar_wait(bar_m, 0);
      wgmma_fence();
#pragma unroll
      for (int kk = 0; kk < 16; kk++)
        if (((kk >> 2) & 1) == 0) {
          wgmma_ss_n32_ta(d3, make_desc(s16 + (uint32_t)kW3 * (kSlot >> 4), kk * 2048, 8192), o_desc(kk), kk != 0);
          wgmma_ss_n32_ta(d4, make_desc(s16 + (uint32_t)kW4 * (kSlot >> 4), kk * 2048, 8192), o_desc(kk), kk != 0);
        }
      wgmma_commit();
    };
    wgmma_wait<1>();
    if (tid == 0) TS(3);
    send_o(C0{});
    if (lane == 0) mbar_arrive_cluster(mapa(bar_lz, peer));
    if (tid == 0) TS(14);
    {
      ldsm_tile(B0, kW3, 3, 2);
      ldsm_tile(B1, kW4, 4, 2);
      wgmma_wait<0>();
      merge(C0{});
      if (tid == 0) TS(20);
      first_half();
      mbar_wait(bar_full + 8 * sv1, par_of(kVT, 15));
      if (tid == 0) TS(29);
      wgmma_fence();
      pv_blk(oA, C1{}, 0);
      pv_blk(oB, C1{}, 16384);
      wgmma_wait<1 + H1LATE>();
      send_o(C1{});
      if (tid == 0) TS(17);
      mbar_wait(bar_w0, 0);
      wgmma_wait<H1LATE>();
      ldsm_tile(B2, kW5, 5, 3);
      merge(C1{});
    }
    if (tid == 0) TS(30);
    zero16(d5);
    mbar_wait_cluster(bar_lz, 0);
    mbar_wait(bar_m2, 0);
    if (tid == 0) TS(4);
    wgmma_fence();
    oproj(d3, B0, 1);
    oproj(d4, B1, 1);
    oproj(d5, B2, 2);
    wgmma_wait<2>();
    fence_arr(d3);
    send_tile(d3, 2);
    mbar_wait(bar_m, 0);
    wgmma_wait<1>();
    fence_arr(d4);
    send_tile(d4, 1);
    if (tid == 0) TS(15);
    mbar_wait(bar_m, 0);
    wgmma_wait<0>();
    fence_arr(d5);
    if (tid == 0) TS(10);
    finish_tile(d5, 0);
  } else {
    asm volatile("barrier.cluster.wait.acquire.aligned;" ::: "memory");
    uint32_t A0[16][4], A1[16][4], A2[16][4];
    auto grab = [&](uint32_t (&A)[16][4], int sl, int ins) {
      ldsm_tile(A, sl, ins, 3);
      __syncwarp();
      if (lane == 0) mbar_arrive(bar_empty + 8 * sl);
    };
#pragma unroll
    for (int kk = 0; kk < 16; kk++)
#pragma unroll
      for (int i = 0; i < 4; i++) { A0[kk][i] = 0u; A1[kk][i] = 0u; A2[kk][i] = 0u; }
    if (tid == 160) {
      asm volatile("ld.relaxed.gpu.global.u32 %0, [%1];" : "=r"(tag) : "l"(g_epoch + b) : "memory");
      asm volatile("st.shared.u32 [%0], %1;" ::"r"(tagw), "r"((tag + 1u) & 1u) : "memory");
      if (cta == 0) asm volatile("st.relaxed.gpu.global.u32 [%0], %1;" ::"l"(g_prog + (tag & 1u)), "r"(0u) : "memory");
    }
    __syncwarp();
    constexpr uint64_t kFirst = 0x12F0000000000000ull, kNormal = 0x1000000000000000ull;
    auto wo_tile = [&](int idx) {
      return (int)((s ? 0x6412530u : 0x2056134u) >> (4 * idx)) & 7;
    };
    auto issue = [&](uint32_t en) {
      const uint32_t slot = en & 7u, kind = (en >> 4) & 3u;
      const int idx = (int)((en >> 6) & 15u);
      const uint32_t fb = bar_full + 8 * slot, dst = sbase + slot * kSlot;
      mbar_wait(bar_empty + 8 * slot, (en >> 3) & 1u);
      if (kind == 2) {
        mbar_expect_tx(bar_wo + 8 * idx, kSlot);
        tma_4d(dst, &tmWo, bar_wo + 8 * idx, wo_tile(idx) * 64, 0, s, hkv * 2);
      } else {
        mbar_expect_tx(fb, kSlot);
        tma_3d_h(dst, kind == 3 ? &tmWq : kind ? &tmV : &tmK, fb, 0, (kind == 3 ? 0 : row0) + idx * 64, kind == 3 ? h * 4 : 0,
                 kind == 3 ? kNormal : kFirst);
      }
    };
#pragma unroll 1
    for (int e = 0; e < THR0 - 2; e++) {
      if (tid == 128) issue(cS.e[e]);
      __syncwarp();
      if (e == kEntR0 + RDELAY) grab(A0, kW0, 0);
      if (e == kEntR1 + RDELAY) grab(A1, kW1, 1);
      if (e == kEntR2 + RDELAY) grab(A2, kW2, 2);
    }
    asm volatile("ld.shared.u32 %0, [%1];" : "=r"(tag) : "r"(tagw) : "memory");
    if (tid == 128) {
      int cnt = 0;
      auto lead = [&](int e) {
        return (e - THR0) * 128 - cnt;
      };
      auto soft_wait = [&](uint32_t bar, uint32_t par, int e, int lim) {
        if (lead(e) > lim) mbar_wait(bar, par);
      };
      auto gate = [&](int e) {
        const uint32_t ge = cS.e[e - 2];
        const bool isw = ((ge >> 4) & 3u) == 2u;
        soft_wait(isw ? bar_wo + 8u * ((ge >> 6) & 15u) : bar_full + 8u * (ge & 7u), ge >> 10, e, -DLO);
        if (!isw) soft_wait(bar_empty + 8u * (ge & 7u), ((ge >> 3) & 1u) ^ 1u, e, DHI);
      };
      auto count = [&]() { asm volatile("atom.relaxed.gpu.global.add.u32 %0, [%1], 1;" : "=r"(cnt) : "l"(g_prog + tag) : "memory"); };
      issue(cS.e[THR0 - 2]);
      issue(cS.e[THR0 - 1]);
      count();
#pragma unroll
      for (int i = 0; i < 7; i++)
        if (((JW >> (48 - 8 * i)) & 255) == 16 && EPF)
          asm volatile("cp.async.bulk.prefetch.tensor.4d.L2.global [%0, {%1, %2, %3, %4}];"
                       ::"l"(&tmWo), "r"(wo_tile(i) * 64), "r"(0), "r"(s), "r"(hkv * 2) : "memory");
#pragma unroll 1
      for (int e = THR0; e < kEntA; e++) {
        gate(e); issue(cS.e[e]); count();
        if (e == ECLR) mbar_arrive(bar_c);
      }
      TS(39);
#pragma unroll 1
      for (int i = 0; i < 2; i++) {
        const uint32_t en = cS.e[kEntA + i], dst = sbase + (en & 7u) * kSlot, fb = bar_full + 8 * (en & 7u);
        gate(kEntA + i);
        if (i) {
          const uint32_t ea = cS.e[kEntA];
          if (lead(kEntA + 1) > -DL2) {
            const uint32_t t0 = (uint32_t)clock();
            while (!mbar_test(bar_full + 8 * (ea & 7u), ea >> 10) && (uint32_t)clock() - t0 < GBT) {}
          }
        }
        mbar_wait(bar_empty + 8 * (en & 7u), (en >> 3) & 1u);
        mbar_expect_tx(fb, kSlot);
        tma_3d_h(dst, &tmV2, fb, 0, row0 + 14 * 64, 2 * (s ^ 1) + i, kFirst);
        tma_3d_h(dst + kSlot / 2, &tmV2, fb, 0, row0 + 14 * 64, 2 * s + i, kFirst);
        TS(35 + i);
        count();
      }
      asm volatile("st.volatile.shared.u32 [%0], %1;" ::"r"(progw + 4), "r"(1u) : "memory");
#pragma unroll 1
      for (int e = kEntA + 2; e < kNEnt; e++) issue(cS.e[e]);
      TS(37);
    } else if (tid == 224 && CTRL) {
      mbar_wait(bar_wo + 8 * 3, 0);
      asm volatile("ld.shared.u32 %0, [%1];" : "=r"(tag) : "r"(tagw) : "memory");
      const unsigned* gp = g_prog + tag;
      unsigned va, vb2, stop = 0;
      asm volatile("ld.relaxed.gpu.global.u32 %0, [%1];" : "=r"(va) : "l"(gp) : "memory");
#pragma unroll 1
      for (uint32_t n = 0; n < kTryLimit && !stop; n++) {
        __nanosleep(PSL);
        asm volatile("ld.relaxed.gpu.global.u32 %0, [%1];" : "=r"(vb2) : "l"(gp) : "memory");
        asm volatile("st.volatile.shared.u32 [%0], %1;" ::"r"(progw), "r"(va) : "memory");
        __nanosleep(PSL);
        asm volatile("ld.relaxed.gpu.global.u32 %0, [%1];" : "=r"(va) : "l"(gp) : "memory");
        asm volatile("st.volatile.shared.u32 [%0], %1;" ::"r"(progw), "r"(vb2) : "memory");
        asm volatile("ld.volatile.shared.u32 %0, [%1];" : "=r"(stop) : "r"(progw + 4) : "memory");
      }
    } else if (warp == 5) {
      mbar_wait(bar_c, 0);
#pragma unroll 4
      for (int i = 0; i < 28; i++) st_b128(part + i * 32 - 32, tag ^ 1u, 0u, 0u, 0u);
      __syncwarp();
      if (lane == 0) mbar_arrive(bar_m);
    }
    __syncwarp();
    float d0[16], d1[16], d2[16];
    zero16(d0); zero16(d1);
    mbar_wait(bar_m, 0);
    asm volatile("ld.shared.u32 %0, [%1];" : "=r"(tag) : "r"(tagw) : "memory");
    if (tid == 128) TS(21);
    wgmma_fence();
    oproj(d0, A0, 0);
    oproj(d1, A1, 0);
    wgmma_wait<0>();
    if (tid == 128) TS(22);
    uint32_t A3[16][4];
    ldsm_tile(A3, kW6, 6, 3);
    mbar_wait_cluster(bar_lz, 0);
    mbar_wait(bar_m2, 0);
    if (tid == 128) TS(24);
    wgmma_fence();
    oproj(d0, A0, 1);
    oproj(d1, A1, 1);
    wgmma_wait<1>();
    fence_arr(d0);
    send_tile(d0, 0);
    wgmma_fence();
    oproj(d0, A2, 2);
    wgmma_wait<1>();
    fence_arr(d1);
    float mh[8], mp[8];
#pragma unroll
    for (int i = 0; i < 8; i++) { mh[i] = s ? d1[8 + i] : d1[i]; mp[i] = s ? d1[i] : d1[8 + i]; }
    send_word(mp, 3, 0);
    fence_arr(mh);
    if (tid == 128) TS(31);
    zero16(d2);
    wgmma_fence();
    oproj(d2, A3, 2);
    wgmma_wait<1>();
    fence_arr(d0);
    finish_tile(d0, 1);
    mbar_wait_cluster(bar_x + 8u * (uint32_t)(12 + w), 0);
    finish_word(mh, 3, 0, s ? 0 : 6);
    mbar_wait(bar_m, 0);
    wgmma_wait<0>();
    fence_arr(d2);
    if (tid == 128) TS(11);
    finish_tile(d2, 2);
  }
  if (tid == 0) TS(5);
  if (tid == 128) TS(19);

  if (h < 14) {
    const int hw = lane >> 4, tw = warp * 16 + (lane & 15);
    const uint4* src0 = g_part + (size_t)(b * kHkv) * kPartW + h * 128;
    const uint4* src = src0 + (size_t)(hw * 4) * kPartW + tw;
    uint4 v[4];
    uint32_t pending = 0xffu, sel = 0xffu;
    uint32_t spins = 0;
    while (true) {
      const uint32_t mine = sel >> (4 * hw);
#pragma unroll
      for (int j = 0; j < 4; j++)
        if (mine & (1u << j)) ld_b128(v[j], src + (size_t)j * kPartW);
      if (tid == 0 && spins == 0) TS(16);
      uint32_t bad = 0;
#pragma unroll
      for (int j = 0; j < 4; j++) bad |= ((v[j].x ^ tag) & 1u) << j;
      bad = __reduce_or_sync(0xffffffffu, bad << (4 * hw));
      pending &= bad | ~sel;
      if (tid == 0 && spins == 0) TS(12);
      if (!pending) break;
      if (++spins > kTryLimit) __trap();
      sel = pending;
      if (__popc(pending) > POLLN) {
        do {
          __nanosleep(POLLS0);
          uint32_t wd = ~tag;
          if ((pending >> lane) & 1u)
            asm volatile("ld.relaxed.gpu.global.u32 %0, [%1];" : "=r"(wd) : "l"(src0 + (size_t)lane * kPartW + warp * 16) : "memory");
          sel = __ballot_sync(0xffffffffu, ((wd ^ tag) & 1u) == 0);
          if (++spins > kTryLimit) __trap();
        } while (!sel);
      }
    }
    if (tid == 0) TS(13);
    if (tid == 128) TS(25);
    float r[8];
#pragma unroll
    for (int e = 0; e < 8; e++) r[e] = 0.f;
#pragma unroll
    for (int j = 0; j < 4; j++) {
      r[0] += __uint_as_float(v[j].x << 16); r[1] += __uint_as_float(v[j].x & 0xffff0000u);
      r[2] += __uint_as_float(v[j].y << 16); r[3] += __uint_as_float(v[j].y & 0xffff0000u);
      r[4] += __uint_as_float(v[j].z << 16); r[5] += __uint_as_float(v[j].z & 0xffff0000u);
      r[6] += __uint_as_float(v[j].w << 16); r[7] += __uint_as_float(v[j].w & 0xffff0000u);
    }
    const float y0 = (hw ? r[4] : r[0]) + __shfl_xor_sync(0xffffffffu, hw ? r[0] : r[4], 16);
    const float y1 = (hw ? r[5] : r[1]) + __shfl_xor_sync(0xffffffffu, hw ? r[1] : r[5], 16);
    const float y2 = (hw ? r[6] : r[2]) + __shfl_xor_sync(0xffffffffu, hw ? r[2] : r[6], 16);
    const float y3 = (hw ? r[7] : r[3]) + __shfl_xor_sync(0xffffffffu, hw ? r[3] : r[7], 16);
    if (h == 0 && tid == 64) asm volatile("st.relaxed.gpu.global.u32 [%0], %1;" ::"l"(g_epoch + b), "r"(tag) : "memory");
    const int q = 8 * (2 * s + hw) + 2 * (tw & 3);
    const int na = 64 * hkv + 16 * (tw >> 5) + ((tw & 31) >> 2), nb = na + 8;
    __nv_bfloat16* op = out + (size_t)(b * kSq + q) * kD;
    op[na] = __float2bfloat16(y0); op[kD + na] = __float2bfloat16(y1);
    op[nb] = __float2bfloat16(y2); op[kD + nb] = __float2bfloat16(y3);
  }
  if (tid == 0) TS(6);
}

typedef CUresult (*EncodeFn)(CUtensorMap*, CUtensorMapDataType, cuuint32_t, void*, const cuuint64_t*, const cuuint64_t*,
                             const cuuint32_t*, const cuuint32_t*, CUtensorMapInterleave, CUtensorMapSwizzle,
                             CUtensorMapL2promotion, CUtensorMapFloatOOBfill);

}

extern "C" void kernel_launch(void* const* d_in, const int* in_sizes, int n_in, void* d_out, int out_size) {
  (void)in_sizes; (void)n_in; (void)out_size;
  static CUtensorMap tmK, tmV, tmX, tmWq, tmWo, tmV2;
  static const void* cached[5] = {nullptr, nullptr, nullptr, nullptr, nullptr};
  static EncodeFn enc = nullptr;
  if (!enc) {
    cudaDriverEntryPointQueryResult qr;
    cudaGetDriverEntryPoint("cuTensorMapEncodeTiled", (void**)&enc, cudaEnableDefault, &qr);
    cudaFuncSetAttribute(fused_attn_kernel, cudaFuncAttributeMaxDynamicSharedMemorySize, (int)kSmemBytes);
  }
  if (cached[0] != d_in[0] || cached[1] != d_in[1] || cached[2] != d_in[2] || cached[3] != d_in[3] || cached[4] != d_in[4]) {
    const cuuint32_t es[4] = {1, 1, 1, 1};
    {
      const cuuint64_t dims[3] = {64, (cuuint64_t)kB * kHkv * kSk, 4};
      const cuuint64_t strides[2] = {kDh * 2, 128};
      const cuuint32_t box[3] = {64, 64, 4};
      enc(&tmK, CU_TENSOR_MAP_DATA_TYPE_BFLOAT16, 3, d_in[1], dims, strides, box, es, CU_TENSOR_MAP_INTERLEAVE_NONE,
          CU_TENSOR_MAP_SWIZZLE_128B, CU_TENSOR_MAP_L2_PROMOTION_L2_256B, CU_TENSOR_MAP_FLOAT_OOB_FILL_NONE);
      enc(&tmV, CU_TENSOR_MAP_DATA_TYPE_BFLOAT16, 3, d_in[2], dims, strides, box, es, CU_TENSOR_MAP_INTERLEAVE_NONE,
          CU_TENSOR_MAP_SWIZZLE_128B, CU_TENSOR_MAP_L2_PROMOTION_L2_256B, CU_TENSOR_MAP_FLOAT_OOB_FILL_NONE);
    }
    {
      const cuuint64_t dims[3] = {64, (cuuint64_t)kB * kHkv * kSk, 4};
      const cuuint64_t strides[2] = {kDh * 2, 128};
      const cuuint32_t box[3] = {64, 128, 1};
      enc(&tmV2, CU_TENSOR_MAP_DATA_TYPE_BFLOAT16, 3, d_in[2], dims, strides, box, es, CU_TENSOR_MAP_INTERLEAVE_NONE,
          CU_TENSOR_MAP_SWIZZLE_128B, CU_TENSOR_MAP_L2_PROMOTION_L2_128B, CU_TENSOR_MAP_FLOAT_OOB_FILL_NONE);
    }
    {
      const cuuint64_t dims[3] = {64, (cuuint64_t)kB * kSq, 7};
      const cuuint64_t strides[2] = {kD * 2, 128};
      const cuuint32_t box[3] = {64, 32, 7};
      enc(&tmX, CU_TENSOR_MAP_DATA_TYPE_BFLOAT16, 3, d_in[0], dims, strides, box, es, CU_TENSOR_MAP_INTERLEAVE_NONE,
          CU_TENSOR_MAP_SWIZZLE_128B, CU_TENSOR_MAP_L2_PROMOTION_L2_128B, CU_TENSOR_MAP_FLOAT_OOB_FILL_NONE);
    }
    {
      const cuuint64_t dims[3] = {64, (cuuint64_t)kD, (cuuint64_t)kHq * kDh / 64};
      const cuuint64_t strides[2] = {(cuuint64_t)kHq * kDh * 2, 128};
      const cuuint32_t box[3] = {64, 64, 4};
      enc(&tmWq, CU_TENSOR_MAP_DATA_TYPE_BFLOAT16, 3, d_in[3], dims, strides, box, es, CU_TENSOR_MAP_INTERLEAVE_NONE,
          CU_TENSOR_MAP_SWIZZLE_128B, CU_TENSOR_MAP_L2_PROMOTION_L2_256B, CU_TENSOR_MAP_FLOAT_OOB_FILL_NONE);
    }
    {
      const cuuint64_t dims[4] = {(cuuint64_t)kD, 128, 2, (cuuint64_t)kHq};
      const cuuint64_t strides[3] = {kD * 2, (cuuint64_t)128 * kD * 2, (cuuint64_t)256 * kD * 2};
      const cuuint32_t box[4] = {64, 128, 1, 2};
      enc(&tmWo, CU_TENSOR_MAP_DATA_TYPE_BFLOAT16, 4, d_in[4], dims, strides, box, es, CU_TENSOR_MAP_INTERLEAVE_NONE,
          CU_TENSOR_MAP_SWIZZLE_128B, CU_TENSOR_MAP_L2_PROMOTION_L2_128B, CU_TENSOR_MAP_FLOAT_OOB_FILL_NONE);
    }
    for (int i = 0; i < 5; i++) cached[i] = d_in[i];
  }
  fused_attn_kernel<<<128, kThreads, kSmemBytes>>>(tmK, tmV, tmX, tmWq, tmWo, tmV2, (__nv_bfloat16*)d_out);
}
```

```cpp
#include <cuda_runtime.h>
#include <cuda.h>
#include <cuda_bf16.h>
#include <stdint.h>
#include <type_traits>

namespace {

constexpr int kB = 8, kSq = 32, kD = 448, kHq = 16, kHkv = 8, kSk = 8192, kDh = 256, kW = 2048;
constexpr uint32_t kSlot = 32768;
constexpr int kNSlot = 6;
constexpr uint32_t kQOff = kNSlot * kSlot;
constexpr uint32_t kMiscOff = kQOff + 32768;
constexpr uint32_t kSmemBytes = kMiscOff + 1024 + 512 + 1024;
constexpr int kThreads = 256;
constexpr int kPartW = 14 * 128;

#define JW 0x01020304050610ull
#define DLO 64
#define DHI 0
#define ECLR 30
#define EVF 1
#define OCLR 0
#define EPF 0
#define B0DELAY 0
#define PSL 200
#define CTRL 0
#define GB 1
#define GBT 100000u
#define DL2 100000
#define WEARLY 0
#define H1LATE 0
#define NPF 0
#define G1 0
#define EK 1
#define TWOP 0
#define PV12E 0
#define INFL 2
#define THR0 20
#define POLLN 8
#define POLLS0 100
#define POLLS1 400
#define RDELAY 3
constexpr int kJW[7] = {(JW >> 48) & 255, (JW >> 40) & 255, (JW >> 32) & 255, (JW >> 24) & 255, (JW >> 16) & 255, (JW >> 8) & 255, JW & 255};
constexpr int kNEnt = 40;
struct Sched {
  uint16_t e[kNEnt];
  uint64_t kt, vt;
  int wslot[7], went[7], ea;
  bool ok;
};
constexpr Sched make_sched() {
  Sched S{};
  int kind[kNEnt] = {}, idx[kNEnt] = {}, n = 0;
  for (int i = 6 - EK; i <= 6; i++) { kind[n] = 3; idx[n++] = i; }
  if (EK < 1) { kind[n] = 0; idx[n++] = 0; }
  for (int i = 0; i < EK; i++) S.kt |= (uint64_t)(5 - EK + i) << (4 * i);
  for (int j = 0; j <= 16; j++) {
    if (j < 13 && j + 1 >= EK) { kind[n] = 0; idx[n++] = j + 1; }
    if (j == 12) { kind[n] = 0; idx[n++] = 14; kind[n] = 0; idx[n++] = 15; }
    for (int i = 0; i < 7; i++) if (kJW[i] == j) { kind[n] = 2; idx[n++] = i; }
    if (j < 16) { kind[n] = 1; idx[n++] = j; }
  }
  S.ok = n == kNEnt;
  int fifo[kNEnt + kNSlot] = {}, head = 0, tail = 0, uses[kNSlot] = {}, fulls[kNSlot] = {}, last[kNSlot] = {};
  for (int i = 0; i < kNSlot; i++) { if (i < 5 - EK) fifo[tail++] = i; uses[i] = 1; fulls[i] = 1; last[i] = -100; }
  for (int e = 0; e < kNEnt; e++) {
    if (e == EK) fifo[tail++] = 5;
    if (e == EK + 1) for (int i = 0; i < EK; i++) fifo[tail++] = 5 - EK + i;
    if (head == tail) { S.ok = false; break; }
    const int sl = fifo[head++];
    if (e - last[sl] <= RDELAY) S.ok = false;
    last[sl] = -100;
    S.e[e] = (uint16_t)(sl | (((uses[sl] - 1) & 1) << 3) | (kind[e] << 4) | (idx[e] << 6));
    uses[sl]++;
    if (kind[e] == 2) {
      S.wslot[idx[e]] = sl; S.went[idx[e]] = e;
      if (idx[e] < 3) { fifo[tail++] = sl; last[sl] = e; }
    } else {
      const uint64_t f = (uint64_t)(sl | ((fulls[sl] & 1) << 3)) << (4 * idx[e]);
      if (kind[e] == 0) S.kt |= f; else if (kind[e] == 1) S.vt |= f;
      if (kind[e] == 1 && idx[e] == 14) S.ea = e;
      S.e[e] = (uint16_t)(S.e[e] | ((fulls[sl] & 1) << 10));
      fulls[sl]++;
      fifo[tail++] = sl;
    }
  }
  for (int i = 3; i < 7; i++)
    if (S.wslot[i] == (int)((S.vt >> 56) & 7) || S.wslot[i] == (int)((S.vt >> 60) & 7)) S.ok = false;
  return S;
}
constexpr Sched kS = make_sched();
static_assert(kS.ok && kS.went[6] == kNEnt - 1, "ring schedule");
__constant__ Sched cS = make_sched();
constexpr uint64_t kKT = kS.kt, kVT = kS.vt;
__host__ __device__ constexpr uint32_t slot_of(uint64_t t, int i) { return (uint32_t)(t >> (4 * i)) & 7u; }
__host__ __device__ constexpr uint32_t par_of(uint64_t t, int i) { return (uint32_t)(t >> (4 * i + 3)) & 1u; }
constexpr uint32_t kSlotV14 = slot_of(kVT, 14);
static_assert(slot_of(kVT, 13) != slot_of(kVT, 14) && slot_of(kVT, 13) != slot_of(kVT, 15) && slot_of(kVT, 14) != slot_of(kVT, 15) &&
              slot_of(kKT, 14) != slot_of(kKT, 15) && slot_of(kKT, 13) != slot_of(kKT, 14), "the end game keeps these tiles at the same time");
constexpr int kEntA = kS.ea;
static_assert(((kS.e[kEntA + 1] >> 4) & 3) == 1 && ((kS.e[kEntA - 1] >> 4) & 3) == 1 &&
              ECLR < kEntA && ECLR >= THR0 && THR0 - 2 > kS.went[2] + RDELAY, "producer phases");
constexpr int kEntR0 = kS.went[0], kEntR1 = kS.went[1], kEntR2 = kS.went[2];
constexpr int kW0 = kS.wslot[0], kW1 = kS.wslot[1], kW2 = kS.wslot[2], kW3 = kS.wslot[3], kW4 = kS.wslot[4], kW5 = kS.wslot[5], kW6 = kS.wslot[6];

__device__ uint4 g_part[kB * kHkv * kPartW];
__device__ unsigned g_epoch[kB];
__device__ unsigned g_prog[2];

__device__ __forceinline__ uint32_t smem_u32(const void* p) { return (uint32_t)__cvta_generic_to_shared(p); }
__device__ __forceinline__ void mbar_init(uint32_t bar, uint32_t cnt) {
  asm volatile("mbarrier.init.shared::cta.b64 [%0], %1;" ::"r"(bar), "r"(cnt) : "memory");
}
__device__ __forceinline__ void mbar_expect_tx(uint32_t bar, uint32_t bytes) {
  asm volatile("mbarrier.arrive.expect_tx.shared::cta.b64 _, [%0], %1;" ::"r"(bar), "r"(bytes) : "memory");
}
__device__ __forceinline__ void mbar_arrive(uint32_t bar) {
  asm volatile("mbarrier.arrive.shared::cta.b64 _, [%0];" ::"r"(bar) : "memory");
}
__device__ __forceinline__ void mbar_arrive_cluster(uint32_t cluster_addr) {
  asm volatile("mbarrier.arrive.relaxed.cluster.shared::cluster.b64 _, [%0];" ::"r"(cluster_addr) : "memory");
}
__device__ __forceinline__ bool mbar_try(uint32_t bar, uint32_t parity) {
  uint32_t ok;
  asm volatile("{\n.reg .pred p;\nmbarrier.try_wait.parity.shared::cta.b64 p, [%1], %2;\nselp.u32 %0, 1, 0, p;\n}\n"
               : "=r"(ok) : "r"(bar), "r"(parity) : "memory");
  return ok != 0;
}
__device__ __forceinline__ bool mbar_test(uint32_t bar, uint32_t parity) {
  uint32_t ok;
  asm volatile("{\n.reg .pred p;\nmbarrier.test_wait.parity.shared::cta.b64 p, [%1], %2;\nselp.u32 %0, 1, 0, p;\n}\n"
               : "=r"(ok) : "r"(bar), "r"(parity) : "memory");
  return ok != 0;
}
__device__ __forceinline__ bool mbar_try_cluster(uint32_t bar, uint32_t parity) {
  uint32_t ok;
  asm volatile("{\n.reg .pred p;\nmbarrier.try_wait.parity.acquire.cluster.shared::cta.b64 p, [%1], %2;\nselp.u32 %0, 1, 0, p;\n}\n"
               : "=r"(ok) : "r"(bar), "r"(parity) : "memory");
  return ok != 0;
}
constexpr long long kSpinLimit = 4000000000ll;
constexpr uint32_t kTryLimit = 1u << 22;
__device__ __forceinline__ void mbar_wait(uint32_t bar, uint32_t parity) {
  uint32_t n = 0;
  while (!mbar_try(bar, parity)) { if (++n > kTryLimit) __trap(); }
}
__device__ __forceinline__ void mbar_wait_cluster(uint32_t bar, uint32_t parity) {
  uint32_t n = 0;
  while (!mbar_try_cluster(bar, parity)) { if (++n > kTryLimit) __trap(); }
}
__device__ __forceinline__ uint32_t mapa(uint32_t addr, uint32_t rank) {
  uint32_t r;
  asm volatile("mapa.shared::cluster.u32 %0, %1, %2;" : "=r"(r) : "r"(addr), "r"(rank));
  return r;
}
__device__ __forceinline__ void tma_3d(uint32_t dst, const CUtensorMap* tm, uint32_t bar, int c0, int c1, int c2) {
  asm volatile("cp.async.bulk.tensor.3d.shared::cluster.global.mbarrier::complete_tx::bytes [%0], [%1, {%3, %4, %5}], [%2];"
               ::"r"(dst), "l"(tm), "r"(bar), "r"(c0), "r"(c1), "r"(c2) : "memory");
}
__device__ __forceinline__ void tma_3d_h(uint32_t dst, const CUtensorMap* tm, uint32_t bar, int c0, int c1, int c2, uint64_t pol) {
  asm volatile("cp.async.bulk.tensor.3d.shared::cluster.global.mbarrier::complete_tx::bytes.L2::cache_hint [%0], [%1, {%3, %4, %5}], [%2], %6;"
               ::"r"(dst), "l"(tm), "r"(bar), "r"(c0), "r"(c1), "r"(c2), "l"(pol) : "memory");
}
__device__ __forceinline__ void tma_4d(uint32_t dst, const CUtensorMap* tm, uint32_t bar, int c0, int c1, int c2, int c3) {
  asm volatile("cp.async.bulk.tensor.4d.shared::cluster.global.mbarrier::complete_tx::bytes [%0], [%1, {%3, %4, %5, %6}], [%2];"
               ::"r"(dst), "l"(tm), "r"(bar), "r"(c0), "r"(c1), "r"(c2), "r"(c3) : "memory");
}
__device__ __forceinline__ void st_b128(uint4* p, uint32_t x, uint32_t y, uint32_t z, uint32_t w) {
  asm volatile("{\n.reg .b128 t;\nmov.b128 t, {%1, %2, %3, %4};\nst.relaxed.gpu.global.b128 [%0], t;\n}\n"
               ::"l"(p), "r"(x), "r"(y), "r"(z), "r"(w) : "memory");
}
__device__ __forceinline__ void ld_b128(uint4& v, const uint4* p) {
  asm volatile("{\n.reg .b128 t;\nld.relaxed.gpu.global.b128 t, [%4];\nmov.b128 {%0, %1, %2, %3}, t;\n}\n"
               : "=r"(v.x), "=r"(v.y), "=r"(v.z), "=r"(v.w) : "l"(p) : "memory");
}
__device__ __forceinline__ bool __syncthreads_and_wg(bool p) {
  uint32_t r;
  asm volatile("{\n.reg .pred a, b;\nsetp.ne.u32 a, %1, 0;\nbar.red.and.pred b, 2, 128, a;\nselp.u32 %0, 1, 0, b;\n}\n"
               : "=r"(r) : "r"((uint32_t)p) : "memory");
  return r != 0;
}
__device__ __forceinline__ void fence_proxy_async() { asm volatile("fence.proxy.async.shared::cta;" ::: "memory"); }
__device__ __forceinline__ void wgmma_fence() { asm volatile("wgmma.fence.sync.aligned;" ::: "memory"); }
__device__ __forceinline__ void wgmma_commit() { asm volatile("wgmma.commit_group.sync.aligned;" ::: "memory"); }
template <int N> __device__ __forceinline__ void wgmma_wait() { asm volatile("wgmma.wait_group.sync.aligned %0;" ::"n"(N) : "memory"); }
__device__ __forceinline__ float ex2(float x) { float y; asm("ex2.approx.ftz.f32 %0, %1;" : "=f"(y) : "f"(x)); return y; }
__device__ __forceinline__ float rcp(float x) { float y; asm("rcp.approx.ftz.f32 %0, %1;" : "=f"(y) : "f"(x)); return y; }
__device__ __forceinline__ uint32_t pack_bf16(float lo, float hi) {
  uint32_t r; asm("cvt.rn.bf16x2.f32 %0, %1, %2;" : "=r"(r) : "f"(hi), "f"(lo)); return r;
}
__device__ __forceinline__ uint64_t make_desc(uint32_t base16, uint32_t off, uint32_t lbo) {
  return ((uint64_t)0x40000040u << 32) | (uint64_t)(base16 + (off >> 4) + ((lbo >> 4) << 16));
}
template <typename T> __device__ __forceinline__ void fence_regs(T& r) { asm volatile("" : "+f"(r)::"memory"); }
template <int OFF> __device__ __forceinline__ void fence_half(float (&a)[64]) {
#pragma unroll
  for (int i = 0; i < 32; i++) fence_regs(a[OFF + i]);
}
template <int N> __device__ __forceinline__ void fence_arr(float (&a)[N]) {
#pragma unroll
  for (int i = 0; i < N; i++) fence_regs(a[i]);
}

__device__ __forceinline__ void wgmma_ss_n64(float (&d)[32], uint64_t da, uint64_t db, int scale_d) {
  asm volatile("{\n.reg .pred p;\nsetp.ne.b32 p, %34, 0;\n"
    "wgmma.mma_async.sync.aligned.m64n64k16.f32.bf16.bf16 {%0, %1, %2, %3, %4, %5, %6, %7, %8, %9, %10, %11, %12, %13, %14, %15, %16, %17, %18, %19, %20, %21, %22, %23, %24, %25, %26, %27, %28, %29, %30, %31}, %32, %33, p, 1, 1, 0, 0;\n}\n"
    : "+f"(d[0]), "+f"(d[1]), "+f"(d[2]), "+f"(d[3]), "+f"(d[4]), "+f"(d[5]), "+f"(d[6]), "+f"(d[7]), "+f"(d[8]), "+f"(d[9]), "+f"(d[10]), "+f"(d[11]), "+f"(d[12]), "+f"(d[13]), "+f"(d[14]), "+f"(d[15]), "+f"(d[16]), "+f"(d[17]), "+f"(d[18]), "+f"(d[19]), "+f"(d[20]), "+f"(d[21]), "+f"(d[22]), "+f"(d[23]), "+f"(d[24]), "+f"(d[25]), "+f"(d[26]), "+f"(d[27]), "+f"(d[28]), "+f"(d[29]), "+f"(d[30]), "+f"(d[31])
    : "l"(da), "l"(db), "r"(scale_d));
}
__device__ __forceinline__ void wgmma_rs_n128_tb(float (&d)[64], uint32_t a0, uint32_t a1, uint32_t a2, uint32_t a3, uint64_t db) {
  asm volatile(
    "wgmma.mma_async.sync.aligned.m64n128k16.f32.bf16.bf16 {%0, %1, %2, %3, %4, %5, %6, %7, %8, %9, %10, %11, %12, %13, %14, %15, %16, %17, %18, %19, %20, %21, %22, %23, %24, %25, %26, %27, %28, %29, %30, %31, %32, %33, %34, %35, %36, %37, %38, %39, %40, %41, %42, %43, %44, %45, %46, %47, %48, %49, %50, %51, %52, %53, %54, %55, %56, %57, %58, %59, %60, %61, %62, %63}, {%64, %65, %66, %67}, %68, 1, 1, 1, 1;\n"
    : "+f"(d[0]), "+f"(d[1]), "+f"(d[2]), "+f"(d[3]), "+f"(d[4]), "+f"(d[5]), "+f"(d[6]), "+f"(d[7]), "+f"(d[8]), "+f"(d[9]), "+f"(d[10]), "+f"(d[11]), "+f"(d[12]), "+f"(d[13]), "+f"(d[14]), "+f"(d[15]), "+f"(d[16]), "+f"(d[17]), "+f"(d[18]), "+f"(d[19]), "+f"(d[20]), "+f"(d[21]), "+f"(d[22]), "+f"(d[23]), "+f"(d[24]), "+f"(d[25]), "+f"(d[26]), "+f"(d[27]), "+f"(d[28]), "+f"(d[29]), "+f"(d[30]), "+f"(d[31]), "+f"(d[32]), "+f"(d[33]), "+f"(d[34]), "+f"(d[35]), "+f"(d[36]), "+f"(d[37]), "+f"(d[38]), "+f"(d[39]), "+f"(d[40]), "+f"(d[41]), "+f"(d[42]), "+f"(d[43]), "+f"(d[44]), "+f"(d[45]), "+f"(d[46]), "+f"(d[47]), "+f"(d[48]), "+f"(d[49]), "+f"(d[50]), "+f"(d[51]), "+f"(d[52]), "+f"(d[53]), "+f"(d[54]), "+f"(d[55]), "+f"(d[56]), "+f"(d[57]), "+f"(d[58]), "+f"(d[59]), "+f"(d[60]), "+f"(d[61]), "+f"(d[62]), "+f"(d[63])
    : "r"(a0), "r"(a1), "r"(a2), "r"(a3), "l"(db));
}
__device__ __forceinline__ void wgmma_rs_n32(float (&d)[16], uint32_t a0, uint32_t a1, uint32_t a2, uint32_t a3, uint64_t db, int scale_d) {
  asm volatile("{\n.reg .pred p;\nsetp.ne.b32 p, %21, 0;\n"
    "wgmma.mma_async.sync.aligned.m64n32k16.f32.bf16.bf16 {%0, %1, %2, %3, %4, %5, %6, %7, %8, %9, %10, %11, %12, %13, %14, %15}, {%16, %17, %18, %19}, %20, p, 1, 1, 0;\n}\n"
    : "+f"(d[0]), "+f"(d[1]), "+f"(d[2]), "+f"(d[3]), "+f"(d[4]), "+f"(d[5]), "+f"(d[6]), "+f"(d[7]), "+f"(d[8]), "+f"(d[9]), "+f"(d[10]), "+f"(d[11]), "+f"(d[12]), "+f"(d[13]), "+f"(d[14]), "+f"(d[15])
    : "r"(a0), "r"(a1), "r"(a2), "r"(a3), "l"(db), "r"(scale_d));
}
__device__ __forceinline__ void wgmma_ss_n32_ta(float (&d)[16], uint64_t da, uint64_t db, int scale_d) {
  asm volatile("{\n.reg .pred p;\nsetp.ne.b32 p, %18, 0;\n"
    "wgmma.mma_async.sync.aligned.m64n32k16.f32.bf16.bf16 {%0, %1, %2, %3, %4, %5, %6, %7, %8, %9, %10, %11, %12, %13, %14, %15}, %16, %17, p, 1, 1, 1, 0;\n}\n"
    : "+f"(d[0]), "+f"(d[1]), "+f"(d[2]), "+f"(d[3]), "+f"(d[4]), "+f"(d[5]), "+f"(d[6]), "+f"(d[7]), "+f"(d[8]), "+f"(d[9]), "+f"(d[10]), "+f"(d[11]), "+f"(d[12]), "+f"(d[13]), "+f"(d[14]), "+f"(d[15])
    : "l"(da), "l"(db), "r"(scale_d));
}

template <int OFF>
__device__ __forceinline__ void wgmma_rs_n64_tb(float (&d)[64], uint32_t a0, uint32_t a1, uint32_t a2, uint32_t a3, uint64_t db) {
  asm volatile(
    "wgmma.mma_async.sync.aligned.m64n64k16.f32.bf16.bf16 {%0, %1, %2, %3, %4, %5, %6, %7, %8, %9, %10, %11, %12, %13, %14, %15, %16, %17, %18, %19, %20, %21, %22, %23, %24, %25, %26, %27, %28, %29, %30, %31}, {%32, %33, %34, %35}, %36, 1, 1, 1, 1;\n"
    : "+f"(d[OFF + 0]), "+f"(d[OFF + 1]), "+f"(d[OFF + 2]), "+f"(d[OFF + 3]), "+f"(d[OFF + 4]), "+f"(d[OFF + 5]), "+f"(d[OFF + 6]), "+f"(d[OFF + 7]), "+f"(d[OFF + 8]), "+f"(d[OFF + 9]), "+f"(d[OFF + 10]), "+f"(d[OFF + 11]), "+f"(d[OFF + 12]), "+f"(d[OFF + 13]), "+f"(d[OFF + 14]), "+f"(d[OFF + 15]), "+f"(d[OFF + 16]), "+f"(d[OFF + 17]), "+f"(d[OFF + 18]), "+f"(d[OFF + 19]), "+f"(d[OFF + 20]), "+f"(d[OFF + 21]), "+f"(d[OFF + 22]), "+f"(d[OFF + 23]), "+f"(d[OFF + 24]), "+f"(d[OFF + 25]), "+f"(d[OFF + 26]), "+f"(d[OFF + 27]), "+f"(d[OFF + 28]), "+f"(d[OFF + 29]), "+f"(d[OFF + 30]), "+f"(d[OFF + 31])
    : "r"(a0), "r"(a1), "r"(a2), "r"(a3), "l"(db));
}

#define TS(i) do {} while (0)

__global__ void __cluster_dims__(2, 1, 1) __launch_bounds__(kThreads, 1)
fused_attn_kernel(const __grid_constant__ CUtensorMap tmK, const __grid_constant__ CUtensorMap tmV,
                  const __grid_constant__ CUtensorMap tmX, const __grid_constant__ CUtensorMap tmWq,
                  const __grid_constant__ CUtensorMap tmWo, const __grid_constant__ CUtensorMap tmV2,
                  __nv_bfloat16* __restrict__ out) {
  extern __shared__ uint8_t smem_raw[];
  const uint32_t sbase = (smem_u32(smem_raw) + 1023u) & ~1023u;
  const uint32_t s16 = (sbase & 0x3FFFFu) >> 4, q16 = s16 + (kQOff >> 4);
  const int tid = threadIdx.x, warp = tid >> 5, lane = tid & 31;
  const int cta = blockIdx.x;
  const int b = cta >> 4, hkv = (cta >> 1) & 7, s = cta & 1;
  const int h = hkv * 2 + s;
  const uint32_t misc = sbase + kMiscOff;
  const uint32_t bar_full = misc, bar_empty = misc + 48, bar_w0 = misc + 96, bar_q = misc + 104, bar_qfree = misc + 112;
  const uint32_t tagw = misc + 120;
  const uint32_t bar_s = misc + 128, bar_wo = misc + 160, bar_o = misc + 224;
  const uint32_t bar_m = misc + 288, bar_lz = misc + 296, bar_m2 = misc + 304, bar_b1 = misc + 312;
  const uint32_t stats = misc + 320, bar_x = misc + 832, bar_c = misc + 960, progw = misc + 968;
  const uint32_t qbase = sbase + kQOff;
  const int row0 = (b * kHkv + hkv) * kSk + (kSk - kW) + s * (kW / 2);

  if (tid == 128) {
    for (int i = 0; i < kNSlot; i++) mbar_init(bar_full + 8 * i, 1);
    mbar_init(bar_w0, 1);
    fence_proxy_async();
    mbar_expect_tx(bar_full + 8 * 5, 7 * 4096);
    tma_3d(sbase + 5 * kSlot, &tmX, bar_full + 8 * 5, 0, b * kSq, 0);
    mbar_expect_tx(bar_w0, kSlot);
    tma_3d(qbase, &tmWq, bar_w0, 0, 0, h * 4);
#pragma unroll 1
    for (int i = 0; i < 5; i++) {
      mbar_expect_tx(bar_full + 8 * i, kSlot);
      if (i < 5 - EK) tma_3d(sbase + i * kSlot, &tmWq, bar_full + 8 * i, 0, (i + 1) * 64, h * 4);
      else tma_3d_h(sbase + i * kSlot, &tmK, bar_full + 8 * i, 0, row0 + (i - 5 + EK) * 64, 0, 0x12F0000000000000ull);
    }
  } else if (tid == 160) {
    for (int i = 0; i < kNSlot; i++) mbar_init(bar_empty + 8 * i, 4);
    for (int i = 0; i < 7; i++) mbar_init(bar_wo + 8 * i, 1);
    mbar_init(bar_q, 1); mbar_init(bar_qfree, 4); mbar_init(bar_m, 5); mbar_init(bar_c, 1); mbar_init(bar_lz, 4);
    mbar_init(bar_m2, 4); mbar_init(bar_b1, 1);
    asm volatile("st.shared.v2.u32 [%0], {%1, %1};" ::"r"(progw), "r"(0u) : "memory");
    for (int i = 0; i < 4; i++) mbar_init(bar_s + 8 * i, 1);
    for (int i = 0; i < 8; i++) mbar_init(bar_o + 8 * i, 1);
    for (int i = 0; i < 16; i++) mbar_init(bar_x + 8 * i, 1);
    mbar_expect_tx(bar_q, 16384);
    for (int i = 0; i < 4; i++) mbar_expect_tx(bar_s + 8 * i, 128);
    for (int i = 0; i < 8; i++) mbar_expect_tx(bar_o + 8 * i, 4096);
    for (int i = 0; i < 16; i++) mbar_expect_tx(bar_x + 8 * i, i < 12 ? 1024 : 512);
    asm volatile("fence.mbarrier_init.release.cluster;" ::: "memory");
    fence_proxy_async();
  } else if (tid >= 192 && tid < 196) {
    asm volatile("prefetch.tensormap [%0];" ::"l"(tid == 192 ? &tmK : tid == 193 ? &tmV : tid == 194 ? &tmWo : &tmV2) : "memory");
  }
  __syncthreads();
  asm volatile("barrier.cluster.arrive.relaxed.aligned;" ::: "memory");

  const int wg = warp >> 2, w = warp & 3, g = lane >> 2, t = lane & 3;
  const uint32_t peer = (uint32_t)(s ^ 1);
  unsigned tag;
  uint4* part = g_part + (size_t)(b * kHkv + hkv) * kPartW + s * 7 * 128 + (tid & 127);

  const uint32_t lz = sbase + (uint32_t)kSlotV14 * kSlot + (uint32_t)(tid & 127) * 16u;
  auto send_word = [&](const float* d, int L, int i) {
    const uint32_t dst = mapa(lz + (uint32_t)L * 4096u + (uint32_t)i * 2048u, peer), rb = mapa(bar_x + 8u * (uint32_t)(4 * L + w), peer);
    asm volatile("st.async.weak.shared::cluster.mbarrier::complete_tx::bytes.v4.b32 [%0], {%1, %2, %3, %4}, [%5];"
                 ::"r"(dst), "r"(pack_bf16(d[0], d[1])), "r"(pack_bf16(d[2], d[3])), "r"(pack_bf16(d[4], d[5])), "r"(pack_bf16(d[6], d[7])), "r"(rb) : "memory");
  };
  auto finish_word = [&](const float* d, int L, int i, int word) {
    uint32_t x0, x1, x2, x3;
    asm volatile("ld.shared.v4.u32 {%0, %1, %2, %3}, [%4];" : "=r"(x0), "=r"(x1), "=r"(x2), "=r"(x3)
                 : "r"(lz + (uint32_t)L * 4096u + (uint32_t)i * 2048u) : "memory");
    const uint32_t off = tag << 16;
    const uint32_t v0 = ((__float_as_uint(d[0] + __uint_as_float(x0 << 16)) - off + 0x10000u) & 0xfffe0000u) + off;
    x0 = __byte_perm(v0, pack_bf16(0.f, d[1] + __uint_as_float(x0 & 0xffff0000u)), 0x7632);
    x1 = pack_bf16(d[2] + __uint_as_float(x1 << 16), d[3] + __uint_as_float(x1 & 0xffff0000u));
    x2 = pack_bf16(d[4] + __uint_as_float(x2 << 16), d[5] + __uint_as_float(x2 & 0xffff0000u));
    x3 = pack_bf16(d[6] + __uint_as_float(x3 << 16), d[7] + __uint_as_float(x3 & 0xffff0000u));
    st_b128(part + word * 128, x0, x1, x2, x3);
  };
  auto send_tile = [&](const float (&d)[16], int L) { send_word(d, L, 0); send_word(d + 8, L, 1); };
  auto finish_tile = [&](const float (&d)[16], int L) {
    mbar_wait_cluster(bar_x + 8u * (uint32_t)(4 * L + w), 0);
    finish_word(d, L, 0, s + 2 * L); finish_word(d + 8, L, 1, s + 2 * L + 1);
  };
  auto o_desc = [&](int kk) {
    return make_desc(q16, (uint32_t)(2 + ((kk >> 2) & 1)) * 8192u + (uint32_t)(kk >> 3) * 4096u + (uint32_t)(kk & 3) * 32u, 16);
  };
  auto ldsm_tile = [&](uint32_t (&A)[16][4], int sl, int ins, int hm) {
    mbar_wait(bar_wo + 8 * ins, 0);
    const uint32_t mi = (uint32_t)lane >> 3;
    const uint32_t k = 8u * (mi >> 1) + ((uint32_t)lane & 7u);
    const uint32_t addr = sbase + (uint32_t)sl * kSlot + k * 128u + ((((uint32_t)(2 * w) + (mi & 1u)) ^ (k & 7u)) << 4);
#pragma unroll
    for (int kk = 0; kk < 16; kk++)
      if ((hm >> ((kk >> 2) & 1)) & 1)
        asm volatile("ldmatrix.sync.aligned.m8n8.x4.trans.shared.b16 {%0, %1, %2, %3}, [%4];"
                     : "=r"(A[kk][0]), "=r"(A[kk][1]), "=r"(A[kk][2]), "=r"(A[kk][3]) : "r"(addr + kk * 2048) : "memory");
  };
  auto oproj = [&](float (&d)[16], const uint32_t (&A)[16][4], int hf) {
#pragma unroll
    for (int kk = 0; kk < 16; kk++)
      if (((kk >> 2) & 1) == hf || hf == 2) wgmma_rs_n32(d, A[kk][0], A[kk][1], A[kk][2], A[kk][3], o_desc(kk), kk != 0);
    wgmma_commit();
  };
  auto oproj_s = [&](float (&d)[16], int sl, int hf) {
#pragma unroll
    for (int kk = 0; kk < 16; kk++)
      if (((kk >> 2) & 1) == hf) wgmma_ss_n32_ta(d, make_desc(s16 + (uint32_t)sl * (kSlot >> 4), kk * 2048, 8192), o_desc(kk), kk != 0);
    wgmma_commit();
  };
  auto zero16 = [&](float (&d)[16]) {
#pragma unroll
    for (int i = 0; i < 16; i++) d[i] = 0.f;
    fence_arr(d);
  };

  if (wg == 0) {
    {
      float a[4][16];
#pragma unroll
      for (int mt = 0; mt < 4; mt++) {
#pragma unroll
        for (int i = 0; i < 16; i++) a[mt][i] = 0.f;
        fence_arr(a[mt]);
      }
      mbar_wait(bar_full + 8 * 5, 0);
#pragma unroll 1
      for (int kt = 0; kt < 7; kt++) {
        const uint32_t sl = kt >= 6 - EK ? (uint32_t)(kt - 6 + EK) : (uint32_t)kt - 1u;
        const uint32_t wb = kt == 0 ? q16 : s16 + sl * (kSlot >> 4);
        const uint32_t xb = s16 + ((5 * kSlot) >> 4) + (uint32_t)kt * 256u;
        mbar_wait(kt == 0 ? bar_w0 : bar_full + 8 * sl, kt >= 6 - EK ? 1 : 0);
        wgmma_fence();
#pragma unroll
        for (int kk = 0; kk < 4; kk++) {
#pragma unroll
          for (int mt = 0; mt < 4; mt++)
            wgmma_ss_n32_ta(a[mt], make_desc(wb, mt * 8192 + kk * 2048, 8192), make_desc(xb, kk * 32, 16), 1);
        }
        wgmma_commit();
        wgmma_wait<1>();
        if (kt == 1) {
          asm volatile("barrier.cluster.wait.acquire.aligned;" ::: "memory");
          if (lane == 0) mbar_arrive_cluster(mapa(bar_qfree, peer));
        } else if (kt > 1 && lane == 0) {
          mbar_arrive(bar_empty + 8 * (kt - 1 >= 6 - EK ? kt - 7 + EK : kt - 2));
        }
      }
      wgmma_wait<0>();
#pragma unroll
      for (int mt = 0; mt < 4; mt++) fence_arr(a[mt]);
      if (lane == 0) { mbar_arrive(bar_empty + 8 * EK); mbar_arrive(bar_empty + 8 * 5); }
      asm volatile("bar.sync 2, 128;" ::: "memory");
      const uint32_t mi = (uint32_t)lane >> 3;
      const uint32_t u = (uint32_t)(2 * w) + (mi & 1u);
#pragma unroll
      for (int mt = 0; mt < 4; mt++) {
#pragma unroll
        for (int j = 0; j < 4; j += 2) {
          const uint32_t r = (uint32_t)(32 * s + 8 * j) + 8u * (mi >> 1) + ((uint32_t)lane & 7u);
          const uint32_t addr = qbase + mt * 8192 + r * 128u + ((u ^ (r & 7u)) << 4);
          const uint32_t y0 = pack_bf16(a[mt][4 * j], a[mt][4 * j + 1]), y1 = pack_bf16(a[mt][4 * j + 2], a[mt][4 * j + 3]);
          const uint32_t y2 = pack_bf16(a[mt][4 * j + 4], a[mt][4 * j + 5]), y3 = pack_bf16(a[mt][4 * j + 6], a[mt][4 * j + 7]);
          asm volatile("stmatrix.sync.aligned.m8n8.x4.trans.shared.b16 [%0], {%1, %2, %3, %4};"
                       ::"r"(addr), "r"(y0), "r"(y1), "r"(y2), "r"(y3) : "memory");
        }
      }
      fence_proxy_async();
      asm volatile("bar.sync 2, 128;" ::: "memory");
      if (tid == 0) {
        mbar_wait_cluster(bar_qfree, 0);
        const uint32_t dst = mapa(qbase + (uint32_t)s * 4096u, peer), rb = mapa(bar_q, peer);
#pragma unroll
        for (int mt = 0; mt < 4; mt++)
          asm volatile("cp.async.bulk.shared::cluster.shared::cta.mbarrier::complete_tx::bytes [%0], [%1], 4096, [%2];"
                       ::"r"(dst + mt * 8192), "r"(qbase + (uint32_t)s * 4096u + mt * 8192), "r"(rb) : "memory");
      }
      __syncwarp();
    }

    const float c = 0.0625f * 1.4426950408889634f;
    float oA[64], oB[64];
    float sc[32];
    uint32_t p[16];
#pragma unroll
    for (int i = 0; i < 64; i++) { oA[i] = 0.f; oB[i] = 0.f; }
#pragma unroll
    for (int i = 0; i < 32; i++) sc[i] = 0.f;
#pragma unroll
    for (int i = 0; i < 16; i++) p[i] = 0u;
    fence_arr(oA); fence_arr(oB); fence_arr(sc);
    float m0 = -INFINITY, m1 = -INFINITY, l0 = 0.f, l1 = 0.f;
    const uint32_t offA = (uint32_t)(s ^ 1) * 1024u, offB = (uint32_t)s * 1024u;
    auto pv_half = [&](float (&o)[64], const uint32_t (&pp)[16], uint32_t vb) {
#pragma unroll
      for (int kk = 0; kk < 4; kk++)
        wgmma_rs_n128_tb(o, pp[4 * kk], pp[4 * kk + 1], pp[4 * kk + 2], pp[4 * kk + 3], make_desc(vb, kk * 2048, 8192));
    };
    auto pv_issue = [&](uint32_t vb) {
      wgmma_fence();
      pv_half(oA, p, vb + offA);
      wgmma_commit();
      pv_half(oB, p, vb + offB);
      wgmma_commit();
    };
    auto qk_issue = [&](float (&d)[32], uint32_t kb, bool fresh = false) {
      uint32_t qd = q16;
      if (fresh) asm volatile("" : "+r"(qd));
      wgmma_fence();
#pragma unroll
      for (int kk = 0; kk < 16; kk++) {
        const uint32_t off = (uint32_t)(kk >> 2) * 8192u + (uint32_t)(kk & 3) * 32u;
        wgmma_ss_n64(d, make_desc(qd, off, 16), make_desc(kb, off, 16), kk != 0);
      }
      wgmma_commit();
    };
    auto softmax = [&](float (&d)[32], float& f0, float& f1) {
      float mx0 = d[0], mx1 = d[2];
#pragma unroll
      for (int j = 0; j < 8; j++) {
        mx0 = fmaxf(mx0, fmaxf(d[4 * j], d[4 * j + 1]));
        mx1 = fmaxf(mx1, fmaxf(d[4 * j + 2], d[4 * j + 3]));
      }
      mx0 = fmaxf(mx0, __shfl_xor_sync(0xffffffffu, mx0, 1)); mx0 = fmaxf(mx0, __shfl_xor_sync(0xffffffffu, mx0, 2));
      mx1 = fmaxf(mx1, __shfl_xor_sync(0xffffffffu, mx1, 1)); mx1 = fmaxf(mx1, __shfl_xor_sync(0xffffffffu, mx1, 2));
      const float n0 = fmaxf(m0, mx0), n1 = fmaxf(m1, mx1);
      f0 = ex2((m0 - n0) * c); f1 = ex2((m1 - n1) * c);
      m0 = n0; m1 = n1;
      const float mc0 = m0 * c, mc1 = m1 * c;
      float s0 = 0.f, s1 = 0.f;
#pragma unroll
      for (int j = 0; j < 8; j++) {
        d[4 * j] = ex2(fmaf(d[4 * j], c, -mc0)); d[4 * j + 1] = ex2(fmaf(d[4 * j + 1], c, -mc0));
        d[4 * j + 2] = ex2(fmaf(d[4 * j + 2], c, -mc1)); d[4 * j + 3] = ex2(fmaf(d[4 * j + 3], c, -mc1));
        s0 += d[4 * j] + d[4 * j + 1]; s1 += d[4 * j + 2] + d[4 * j + 3];
      }
      l0 = fmaf(l0, f0, s0); l1 = fmaf(l1, f1, s1);
    };
    auto scale = [&](float (&o)[64], float f0, float f1) {
#pragma unroll
      for (int j = 0; j < 16; j++) { o[4 * j] *= f0; o[4 * j + 1] *= f0; o[4 * j + 2] *= f1; o[4 * j + 3] *= f1; }
    };

    if (tid == 0) TS(26);
    mbar_wait_cluster(bar_q, 0);
    if (tid == 0) TS(34);
#pragma unroll 1
    for (int it = 0; it < 13; it++) {
      const uint32_t ke = (uint32_t)(kKT >> (4 * it)), ks = ke & 7u;
      mbar_wait(bar_full + 8 * ks, (ke >> 3) & 1u);
      if (tid == 0) TS(48 + it);
      qk_issue(sc, s16 + ks * (kSlot >> 4));
      uint32_t vs = ks;
      bool held = it > 0;
      if (it > 0) {
        const uint32_t ve = (uint32_t)(kVT >> (4 * it - 4)), phase = (ve >> 3) & 1u;
        vs = ve & 7u;
        if (!__all_sync(0xffffffffu, mbar_test(bar_full + 8 * vs, phase))) {
          wgmma_wait<0>();
          if (lane == 0) mbar_arrive(bar_empty + 8 * ks);
          held = false;
          mbar_wait(bar_full + 8 * vs, phase);
        }
      }
      pv_issue(s16 + vs * (kSlot >> 4));
      wgmma_wait<2>();
      fence_arr(sc);
      if (lane == 0 && held) mbar_arrive(bar_empty + 8 * ks);
      float f0, f1;
      softmax(sc, f0, f1);
      fence_arr(sc);
      mbar_wait(bar_w0, 0);
      wgmma_wait<0>();
      fence_arr(oA); fence_arr(oB);
      if (lane == 0) mbar_arrive(bar_empty + 8 * vs);
      if (__any_sync(0xffffffffu, (f0 != 1.f) || (f1 != 1.f))) { scale(oA, f0, f1); scale(oB, f0, f1); }
#pragma unroll
      for (int j = 0; j < 8; j++) {
        p[2 * j] = pack_bf16(sc[4 * j], sc[4 * j + 1]);
        p[2 * j + 1] = pack_bf16(sc[4 * j + 2], sc[4 * j + 3]);
      }
    }
    uint32_t pa[32], pq[32];
    float F0, F1, fc0, fc1;
    uint32_t p2[16];
    constexpr uint32_t sv12 = slot_of(kVT, 12);
    const uint32_t land = qbase + (uint32_t)w * 2048u + (uint32_t)lane * 16u;
    {
      constexpr uint32_t k13 = slot_of(kKT, 13), k14 = slot_of(kKT, 14), k15 = slot_of(kKT, 15);
      float sb[32];
#pragma unroll
      for (int i = 0; i < 32; i++) sb[i] = 0.f;
      fence_arr(sb);
      mbar_wait(bar_full + 8 * k13, par_of(kKT, 13));
      if (tid == 0) TS(61);
      qk_issue(sb, s16 + k13 * (kSlot >> 4), true);
      bool held = true;
      if (!__all_sync(0xffffffffu, mbar_test(bar_full + 8 * k14, par_of(kKT, 14)))) {
        wgmma_wait<0>();
        if (lane == 0) mbar_arrive(bar_empty + 8 * k13);
        held = false;
        mbar_wait(bar_full + 8 * k14, par_of(kKT, 14));
      }
      if (tid == 0) TS(1);
      qk_issue(sc, s16 + k14 * (kSlot >> 4), true);
      wgmma_wait<1>();
      fence_arr(sb);
      if (lane == 0 && held) mbar_arrive(bar_empty + 8 * k13);
      softmax(sb, fc0, fc1);
#pragma unroll
      for (int j = 0; j < 8; j++) {
        p2[2 * j] = pack_bf16(sb[4 * j], sb[4 * j + 1]);
        p2[2 * j + 1] = pack_bf16(sb[4 * j + 2], sb[4 * j + 3]);
      }
#pragma unroll
      for (int j = 0; j < 16; j++) asm volatile("" : "+r"(p2[j]));
      asm volatile("" : "+f"(l0), "+f"(l1), "+f"(fc0), "+f"(fc1));
      held = true;
      if (!__all_sync(0xffffffffu, mbar_test(bar_full + 8 * k15, par_of(kKT, 15)))) {
        wgmma_wait<0>();
        if (lane == 0) mbar_arrive(bar_empty + 8 * k14);
        held = false;
        mbar_wait(bar_full + 8 * k15, par_of(kKT, 15));
      }
      if (tid == 0) TS(27);
      qk_issue(sb, s16 + k15 * (kSlot >> 4), true);
      wgmma_wait<1>();
      fence_arr(sc);
      if (lane == 0 && held) mbar_arrive(bar_empty + 8 * k14);
      float fa0, fa1, fb0, fb1;
      softmax(sc, fa0, fa1);
      fence_arr(sc);
      mbar_wait(bar_w0, 0);
      wgmma_wait<0>();
      fence_arr(sb);
      if (lane == 0) mbar_arrive(bar_empty + 8 * k15);
      softmax(sb, fb0, fb1);
      l0 += __shfl_xor_sync(0xffffffffu, l0, 1); l0 += __shfl_xor_sync(0xffffffffu, l0, 2);
      l1 += __shfl_xor_sync(0xffffffffu, l1, 1); l1 += __shfl_xor_sync(0xffffffffu, l1, 2);
      const uint32_t sp = mapa(stats + (uint32_t)(16 * w + g) * 8u, peer), rb = mapa(bar_s + 8 * w, peer);
      if (t == 0) {
        asm volatile("st.async.weak.shared::cluster.mbarrier::complete_tx::bytes.v2.f32 [%0], {%1, %2}, [%3];" ::"r"(sp), "f"(m0), "f"(l0), "r"(rb) : "memory");
        asm volatile("st.async.weak.shared::cluster.mbarrier::complete_tx::bytes.v2.f32 [%0], {%1, %2}, [%3];" ::"r"(sp + 64u), "f"(m1), "f"(l1), "r"(rb) : "memory");
      }
      __syncwarp();
      if (tid == 0) TS(7);
      if (tid == 0) TS(2);
      mbar_wait_cluster(bar_s + 8 * w, 0);
      float pm0, pl0, pm1, pl1;
      asm volatile("ld.shared.v2.f32 {%0, %1}, [%2];" : "=f"(pm0), "=f"(pl0) : "r"(stats + (uint32_t)(16 * w + g) * 8u) : "memory");
      asm volatile("ld.shared.v2.f32 {%0, %1}, [%2];" : "=f"(pm1), "=f"(pl1) : "r"(stats + (uint32_t)(16 * w + g + 8) * 8u) : "memory");
      const float M0 = fmaxf(m0, pm0), M1 = fmaxf(m1, pm1);
      const float e0 = ex2((m0 - M0) * c), e1 = ex2((m1 - M1) * c);
      const float g0 = ex2((pm0 - M0) * c), g1 = ex2((pm1 - M1) * c);
      const float r0 = e0 * rcp(l0 * e0 + pl0 * g0), r1 = e1 * rcp(l1 * e1 + pl1 * g1);
      fb0 *= r0; fb1 *= r1;
#pragma unroll
      for (int j = 0; j < 8; j++) {
        pa[2 * j] = pack_bf16(sc[4 * j] * fb0, sc[4 * j + 1] * fb0);
        pa[2 * j + 1] = pack_bf16(sc[4 * j + 2] * fb1, sc[4 * j + 3] * fb1);
        pa[16 + 2 * j] = pack_bf16(sb[4 * j] * r0, sb[4 * j + 1] * r0);
        pa[17 + 2 * j] = pack_bf16(sb[4 * j + 2] * r1, sb[4 * j + 3] * r1);
      }
      F0 = fa0 * fb0; F1 = fa1 * fb1;
      const uint32_t dst = mapa(land + 16384u, peer), pbar = mapa(bar_o + 8 * (4 + w), peer);
#pragma unroll
      for (int i = 0; i < 8; i++)
        asm volatile("st.async.weak.shared::cluster.mbarrier::complete_tx::bytes.v4.b32 [%0], {%1, %2, %3, %4}, [%5];"
                     ::"r"(dst + (i >> 2) * 8192 + (i & 3) * 512), "r"(pa[4 * i]), "r"(pa[4 * i + 1]), "r"(pa[4 * i + 2]), "r"(pa[4 * i + 3]),
                       "r"(pbar) : "memory");
    }
    constexpr uint32_t sv13 = slot_of(kVT, 13), sv0 = slot_of(kVT, 14), sv1 = slot_of(kVT, 15);
    using C0 = std::integral_constant<int, 0>;
    using C1 = std::integral_constant<int, 1>;
    if (tid == 0) TS(8);
    mbar_wait(bar_full + 8 * sv12, par_of(kVT, 12));
    pv_issue(s16 + sv12 * (kSlot >> 4));
    wgmma_wait<0>();
    fence_arr(oA); fence_arr(oB);
    if (lane == 0) mbar_arrive(bar_empty + 8 * sv12);
    if (__any_sync(0xffffffffu, (fc0 != 1.f) || (fc1 != 1.f))) { scale(oA, fc0, fc1); scale(oB, fc0, fc1); }
    fence_arr(oA); fence_arr(oB);
    mbar_wait(bar_full + 8 * sv13, par_of(kVT, 13));
    if (tid == 0) TS(23);
    wgmma_fence();
    pv_half(oA, p2, s16 + sv13 * (kSlot >> 4) + offA);
    wgmma_commit();
    pv_half(oB, p2, s16 + sv13 * (kSlot >> 4) + offB);
    wgmma_commit();
    wgmma_wait<1>();
    fence_arr(oA);
    {
      const uint32_t dst = mapa(land, peer), rb = mapa(bar_o + 8 * w, peer);
#pragma unroll
      for (int i = 0; i < 8; i++) {
        const float* o = oA + 8 * i;
        asm volatile("st.async.weak.shared::cluster.mbarrier::complete_tx::bytes.v4.b32 [%0], {%1, %2, %3, %4}, [%5];"
                     ::"r"(dst + (i >> 2) * 8192 + (i & 3) * 512), "r"(pack_bf16(o[0] * F0, o[1] * F0)), "r"(pack_bf16(o[2] * F1, o[3] * F1)),
                       "r"(pack_bf16(o[4] * F0, o[5] * F0)), "r"(pack_bf16(o[6] * F1, o[7] * F1)), "r"(rb) : "memory");
      }
    }
    if (tid == 0) TS(14);
    mbar_wait_cluster(bar_o + 8 * (4 + w), 0);
#pragma unroll
    for (int i = 0; i < 8; i++)
      asm volatile("ld.shared.v4.u32 {%0, %1, %2, %3}, [%4];" : "=r"(pq[4 * i]), "=r"(pq[4 * i + 1]), "=r"(pq[4 * i + 2]), "=r"(pq[4 * i + 3])
                   : "r"(land + 16384u + (i >> 2) * 8192 + (i & 3) * 512) : "memory");
    asm volatile("ld.shared.u32 %0, [%1];" : "=r"(tag) : "r"(tagw) : "memory");
    wgmma_wait<0>();
    fence_arr(oB);
    if (lane == 0) mbar_arrive(bar_empty + 8 * sv13);
    scale(oB, F0, F1);
    fence_arr(oB);
    auto add_peer = [&](auto hc) {
      constexpr int H = decltype(hc)::value;
#pragma unroll
      for (int i = 4 * H; i < 4 * H + 4; i++) {
        uint32_t x[4];
        asm volatile("ld.shared.v4.u32 {%0, %1, %2, %3}, [%4];" : "=r"(x[0]), "=r"(x[1]), "=r"(x[2]), "=r"(x[3])
                     : "r"(land + (i >> 2) * 8192 + (i & 3) * 512) : "memory");
#pragma unroll
        for (int e = 0; e < 4; e++) {
          oB[8 * i + 2 * e] += __uint_as_float(x[e] << 16);
          oB[8 * i + 2 * e + 1] += __uint_as_float(x[e] & 0xffff0000u);
        }
      }
    };
    auto pv_blk = [&](auto hc) {
      constexpr int H = decltype(hc)::value;
      const uint32_t vv = s16 + (H ? sv1 : sv0) * (kSlot >> 4);
      wgmma_fence();
#pragma unroll
      for (int kk = 0; kk < 8; kk++)
        wgmma_rs_n64_tb<32 * H>(oB, pa[4 * kk], pa[4 * kk + 1], pa[4 * kk + 2], pa[4 * kk + 3], make_desc(vv, kk * 2048, 16384));
#pragma unroll
      for (int kk = 0; kk < 8; kk++)
        wgmma_rs_n64_tb<32 * H>(oB, pq[4 * kk], pq[4 * kk + 1], pq[4 * kk + 2], pq[4 * kk + 3], make_desc(vv, 16384 + kk * 2048, 16384));
      wgmma_commit();
    };
    auto put_o = [&](auto hc) {
      constexpr int H = decltype(hc)::value;
      fence_half<32 * H>(oB);
      const uint32_t mi = (uint32_t)lane >> 3;
      const uint32_t r = (uint32_t)(16 * w) + 8u * (mi & 1u) + ((uint32_t)lane & 7u);
#pragma unroll
      for (int i = 0; i < 4; i++) {
        const float* o = oB + 32 * H + 8 * i;
        const uint32_t u = (uint32_t)(2 * i) + (mi >> 1);
        const uint32_t addr = qbase + (uint32_t)(2 + H) * 8192u + r * 128u + ((u ^ (r & 7u)) << 4);
        asm volatile("stmatrix.sync.aligned.m8n8.x4.shared.b16 [%0], {%1, %2, %3, %4};" ::"r"(addr), "r"(pack_bf16(o[0], o[1])),
                     "r"(pack_bf16(o[2], o[3])), "r"(pack_bf16(o[4], o[5])), "r"(pack_bf16(o[6], o[7])) : "memory");
      }
      fence_proxy_async();
      __syncwarp();
      if (lane == 0) mbar_arrive(H ? bar_m2 : bar_m);
    };
    float d3[16], d4[16], d5[16];
    uint32_t B0[16][4], B1[16][4], B2[16][4];
    auto first_half = [&]() {
      zero16(d3); zero16(d4); zero16(d5);
      mbar_wait(bar_wo + 8 * 3, 0);
      mbar_wait(bar_wo + 8 * 4, 0);
      mbar_wait(bar_wo + 8 * 5, 0);
      mbar_wait(bar_m, 0);
      wgmma_fence();
#pragma unroll
      for (int kk = 0; kk < 16; kk++)
        if (((kk >> 2) & 1) == 0) {
          wgmma_ss_n32_ta(d3, make_desc(s16 + (uint32_t)kW3 * (kSlot >> 4), kk * 2048, 8192), o_desc(kk), kk != 0);
          wgmma_ss_n32_ta(d4, make_desc(s16 + (uint32_t)kW4 * (kSlot >> 4), kk * 2048, 8192), o_desc(kk), kk != 0);
          wgmma_ss_n32_ta(d5, make_desc(s16 + (uint32_t)kW5 * (kSlot >> 4), kk * 2048, 8192), o_desc(kk), kk != 0);
        }
      wgmma_commit();
    };
    mbar_wait(bar_full + 8 * sv0, par_of(kVT, 14));
    if (tid == 0) TS(28);
    pv_blk(C0{});
    ldsm_tile(B0, kW3, 3, 2);
    ldsm_tile(B1, kW4, 4, 2);
    mbar_wait_cluster(bar_o + 8 * w, 0);
    if (tid == 0) TS(9);
    wgmma_wait<0>();
    fence_arr(oB);
    if (tid == 0) TS(3);
    add_peer(C0{});
    put_o(C0{});
    add_peer(C1{});
    fence_arr(oB);
    if (lane == 0) mbar_arrive_cluster(mapa(bar_lz, peer));
    if (tid == 0) TS(20);
    {
      first_half();
      mbar_wait(bar_full + 8 * sv1, par_of(kVT, 15));
      if (tid == 0) TS(29);
      pv_blk(C1{});
      wgmma_wait<0>();
      if (tid == 0) TS(17);
      put_o(C1{});
    }
    ldsm_tile(B2, kW5, 5, 2);
    if (tid == 0) TS(30);
    mbar_wait_cluster(bar_lz, 0);
    mbar_wait(bar_m2, 0);
    if (tid == 0) TS(4);
    wgmma_fence();
    oproj(d3, B0, 1);
    oproj(d4, B1, 1);
    wgmma_wait<1>();
    fence_arr(d3);
    send_tile(d3, 2);
    wgmma_fence();
    oproj(d5, B2, 1);
    wgmma_wait<1>();
    fence_arr(d4);
    send_tile(d4, 1);
    if (tid == 0) TS(15);
    mbar_wait(bar_m, 0);
    wgmma_wait<0>();
    fence_arr(d5);
    if (tid == 0) TS(10);
    finish_tile(d5, 0);
  } else {
    asm volatile("barrier.cluster.wait.acquire.aligned;" ::: "memory");
    uint32_t A0[16][4], A1[16][4], A2[16][4];
    auto grab = [&](uint32_t (&A)[16][4], int sl, int ins) {
      ldsm_tile(A, sl, ins, 3);
      __syncwarp();
      if (lane == 0) mbar_arrive(bar_empty + 8 * sl);
    };
#pragma unroll
    for (int kk = 0; kk < 16; kk++)
#pragma unroll
      for (int i = 0; i < 4; i++) { A0[kk][i] = 0u; A1[kk][i] = 0u; A2[kk][i] = 0u; }
    if (tid == 160) {
      asm volatile("ld.relaxed.gpu.global.u32 %0, [%1];" : "=r"(tag) : "l"(g_epoch + b) : "memory");
      asm volatile("st.shared.u32 [%0], %1;" ::"r"(tagw), "r"((tag + 1u) & 1u) : "memory");
      if (cta == 0) asm volatile("st.relaxed.gpu.global.u32 [%0], %1;" ::"l"(g_prog + (tag & 1u)), "r"(0u) : "memory");
    }
    __syncwarp();
    constexpr uint64_t kFirst = 0x12F0000000000000ull, kNormal = 0x1000000000000000ull;
    auto wo_tile = [&](int idx) {
      return (int)((s ? 0x6412530u : 0x2056134u) >> (4 * idx)) & 7;
    };
    auto issue = [&](uint32_t en) {
      const uint32_t slot = en & 7u, kind = (en >> 4) & 3u;
      const int idx = (int)((en >> 6) & 15u);
      const uint32_t fb = bar_full + 8 * slot, dst = sbase + slot * kSlot;
      mbar_wait(bar_empty + 8 * slot, (en >> 3) & 1u);
      if (kind == 2) {
        mbar_expect_tx(bar_wo + 8 * idx, kSlot);
        tma_4d(dst, &tmWo, bar_wo + 8 * idx, wo_tile(idx) * 64, 0, s, hkv * 2);
      } else {
        mbar_expect_tx(fb, kSlot);
        tma_3d_h(dst, kind == 3 ? &tmWq : kind ? &tmV : &tmK, fb, 0, (kind == 3 ? 0 : row0) + idx * 64, kind == 3 ? h * 4 : 0,
                 kind == 3 ? kNormal : kFirst);
      }
    };
#pragma unroll 1
    for (int e = 0; e < THR0 - 2; e++) {
      if (tid == 128) issue(cS.e[e]);
      __syncwarp();
      if (e == kEntR0 + RDELAY) grab(A0, kW0, 0);
      if (e == kEntR1 + RDELAY) grab(A1, kW1, 1);
      if (e == kEntR2 + RDELAY) grab(A2, kW2, 2);
    }
    asm volatile("ld.shared.u32 %0, [%1];" : "=r"(tag) : "r"(tagw) : "memory");
    if (tid == 128) {
      int cnt = 0;
      auto lead = [&](int e) {
        return (e - THR0) * 128 - cnt;
      };
      auto soft_wait = [&](uint32_t bar, uint32_t par, int e, int lim) {
        if (lead(e) > lim) mbar_wait(bar, par);
      };
      auto gate = [&](int e) {
        const uint32_t ge = cS.e[e - 2];
        const bool isw = ((ge >> 4) & 3u) == 2u;
        soft_wait(isw ? bar_wo + 8u * ((ge >> 6) & 15u) : bar_full + 8u * (ge & 7u), ge >> 10, e, -DLO);
        if (!isw) soft_wait(bar_empty + 8u * (ge & 7u), ((ge >> 3) & 1u) ^ 1u, e, DHI);
      };
      auto count = [&]() { asm volatile("atom.relaxed.gpu.global.add.u32 %0, [%1], 1;" : "=r"(cnt) : "l"(g_prog + tag) : "memory"); };
      issue(cS.e[THR0 - 2]);
      issue(cS.e[THR0 - 1]);
      count();
#pragma unroll
      for (int i = 0; i < 7; i++)
        if (((JW >> (48 - 8 * i)) & 255) == 16 && EPF)
          asm volatile("cp.async.bulk.prefetch.tensor.4d.L2.global [%0, {%1, %2, %3, %4}];"
                       ::"l"(&tmWo), "r"(wo_tile(i) * 64), "r"(0), "r"(s), "r"(hkv * 2) : "memory");
#pragma unroll 1
      for (int e = THR0; e < kEntA; e++) {
        gate(e); issue(cS.e[e]); count();
        if (e == ECLR) mbar_arrive(bar_c);
      }
      TS(39);
      constexpr uint32_t ea = kS.e[kEntA], eb = kS.e[kEntA + 1];
      const uint32_t fa = bar_full + 8 * (ea & 7u), fb = bar_full + 8 * (eb & 7u);
      gate(kEntA);
      mbar_wait(bar_empty + 8 * (ea & 7u), (ea >> 3) & 1u);
      mbar_expect_tx(fa, kSlot);
      tma_3d_h(sbase + (ea & 7u) * kSlot, &tmV2, fa, 0, row0 + 14 * 64, 2 * s, kFirst);
      tma_3d_h(sbase + (ea & 7u) * kSlot + kSlot / 2, &tmV2, fa, 0, (row0 ^ (kW / 2)) + 14 * 64, 2 * s, kFirst);
      TS(35);
      asm volatile("red.relaxed.gpu.global.add.u32 [%0], 1;" ::"l"(g_prog + tag) : "memory");
      mbar_wait(bar_empty + 8 * (eb & 7u), (eb >> 3) & 1u);
      mbar_expect_tx(fb, kSlot);
      if (lead(kEntA) > -DL2) mbar_wait(fa, ea >> 10);
      tma_3d_h(sbase + (eb & 7u) * kSlot, &tmV2, fb, 0, row0 + 14 * 64, 2 * s + 1, kFirst);
      tma_3d_h(sbase + (eb & 7u) * kSlot + kSlot / 2, &tmV2, fb, 0, (row0 ^ (kW / 2)) + 14 * 64, 2 * s + 1, kFirst);
      TS(36);
      asm volatile("red.relaxed.gpu.global.add.u32 [%0], 1;" ::"l"(g_prog + tag) : "memory");
#pragma unroll 1
      for (int e = kEntA + 2; e < kNEnt; e++) issue(cS.e[e]);
      TS(37);
    } else if (tid == 224 && CTRL) {
      mbar_wait(bar_wo + 8 * 3, 0);
      asm volatile("ld.shared.u32 %0, [%1];" : "=r"(tag) : "r"(tagw) : "memory");
      const unsigned* gp = g_prog + tag;
      unsigned va, vb2, stop = 0;
      asm volatile("ld.relaxed.gpu.global.u32 %0, [%1];" : "=r"(va) : "l"(gp) : "memory");
#pragma unroll 1
      for (uint32_t n = 0; n < kTryLimit && !stop; n++) {
        __nanosleep(PSL);
        asm volatile("ld.relaxed.gpu.global.u32 %0, [%1];" : "=r"(vb2) : "l"(gp) : "memory");
        asm volatile("st.volatile.shared.u32 [%0], %1;" ::"r"(progw), "r"(va) : "memory");
        __nanosleep(PSL);
        asm volatile("ld.relaxed.gpu.global.u32 %0, [%1];" : "=r"(va) : "l"(gp) : "memory");
        asm volatile("st.volatile.shared.u32 [%0], %1;" ::"r"(progw), "r"(vb2) : "memory");
        asm volatile("ld.volatile.shared.u32 %0, [%1];" : "=r"(stop) : "r"(progw + 4) : "memory");
      }
    } else if (warp == 5) {
      mbar_wait(bar_c, 0);
#pragma unroll 4
      for (int i = 0; i < 28; i++) st_b128(part + i * 32 - 32, tag ^ 1u, 0u, 0u, 0u);
      __syncwarp();
      if (lane == 0) mbar_arrive(bar_m);
    }
    __syncwarp();
    float d0[16], d1[16], d2[16], d3[16];
    zero16(d0); zero16(d1);
    mbar_wait(bar_m, 0);
    asm volatile("ld.shared.u32 %0, [%1];" : "=r"(tag) : "r"(tagw) : "memory");
    if (tid == 128) TS(21);
    wgmma_fence();
    oproj(d0, A0, 0);
    oproj(d1, A1, 0);
    wgmma_wait<1>();
    zero16(d2);
    wgmma_fence();
    oproj(d2, A2, 0);
    wgmma_wait<0>();
    if (tid == 128) TS(22);
    uint32_t A3[16][4];
    ldsm_tile(A3, kW6, 6, 3);
    zero16(d3);
    wgmma_fence();
    oproj(d3, A3, 0);
    mbar_wait_cluster(bar_lz, 0);
    mbar_wait(bar_m2, 0);
    if (tid == 128) TS(24);
    wgmma_fence();
    oproj(d0, A0, 1);
    oproj(d1, A1, 1);
    wgmma_wait<1>();
    fence_arr(d0);
    send_tile(d0, 0);
    wgmma_fence();
    oproj(d2, A2, 1);
    wgmma_wait<1>();
    fence_arr(d1);
    float mh[8], mp[8];
#pragma unroll
    for (int i = 0; i < 8; i++) { mh[i] = s ? d1[8 + i] : d1[i]; mp[i] = s ? d1[i] : d1[8 + i]; }
    send_word(mp, 3, 0);
    fence_arr(mh);
    if (tid == 128) TS(31);
    wgmma_fence();
    oproj(d3, A3, 1);
    wgmma_wait<0>();
    fence_arr(d2); fence_arr(d3);
    if (tid == 128) TS(11);
    finish_tile(d3, 2);
    finish_tile(d2, 1);
    mbar_wait_cluster(bar_x + 8u * (uint32_t)(12 + w), 0);
    finish_word(mh, 3, 0, s ? 0 : 6);
  }
  if (tid == 0) TS(5);
  if (tid == 128) TS(19);

  if (h < 14) {
    const int hw = lane >> 4, tw = warp * 16 + (lane & 15);
    const uint4* src0 = g_part + (size_t)(b * kHkv) * kPartW + h * 128;
    const uint4* src = src0 + (size_t)(hw * 4) * kPartW + tw;
    uint4 v[4];
    uint32_t pending = 0xffu, sel = 0xffu;
    uint32_t spins = 0;
    while (true) {
      const uint32_t mine = sel >> (4 * hw);
#pragma unroll
      for (int j = 0; j < 4; j++)
        if (mine & (1u << j)) ld_b128(v[j], src + (size_t)j * kPartW);
      if (tid == 0 && spins == 0) TS(16);
      uint32_t bad = 0;
#pragma unroll
      for (int j = 0; j < 4; j++) bad |= ((v[j].x ^ tag) & 1u) << j;
      bad = __reduce_or_sync(0xffffffffu, bad << (4 * hw));
      pending &= bad | ~sel;
      if (tid == 0 && spins == 0) TS(12);
      if (!pending) break;
      if (++spins > kTryLimit) __trap();
      sel = pending;
      if (__popc(pending) > POLLN) {
        do {
          __nanosleep(POLLS0);
          uint32_t wd = ~tag;
          if ((pending >> lane) & 1u)
            asm volatile("ld.relaxed.gpu.global.u32 %0, [%1];" : "=r"(wd) : "l"(src0 + (size_t)lane * kPartW + warp * 16) : "memory");
          sel = __ballot_sync(0xffffffffu, ((wd ^ tag) & 1u) == 0);
          if (++spins > kTryLimit) __trap();
        } while (!sel);
      }
    }
    if (tid == 0) TS(13);
    if (tid == 128) TS(25);
    float r[8];
#pragma unroll
    for (int e = 0; e < 8; e++) r[e] = 0.f;
#pragma unroll
    for (int j = 0; j < 4; j++) {
      r[0] += __uint_as_float(v[j].x << 16); r[1] += __uint_as_float(v[j].x & 0xffff0000u);
      r[2] += __uint_as_float(v[j].y << 16); r[3] += __uint_as_float(v[j].y & 0xffff0000u);
      r[4] += __uint_as_float(v[j].z << 16); r[5] += __uint_as_float(v[j].z & 0xffff0000u);
      r[6] += __uint_as_float(v[j].w << 16); r[7] += __uint_as_float(v[j].w & 0xffff0000u);
    }
    const float y0 = (hw ? r[4] : r[0]) + __shfl_xor_sync(0xffffffffu, hw ? r[0] : r[4], 16);
    const float y1 = (hw ? r[5] : r[1]) + __shfl_xor_sync(0xffffffffu, hw ? r[1] : r[5], 16);
    const float y2 = (hw ? r[6] : r[2]) + __shfl_xor_sync(0xffffffffu, hw ? r[2] : r[6], 16);
    const float y3 = (hw ? r[7] : r[3]) + __shfl_xor_sync(0xffffffffu, hw ? r[3] : r[7], 16);
    if (h == 0 && tid == 64) asm volatile("st.relaxed.gpu.global.u32 [%0], %1;" ::"l"(g_epoch + b), "r"(tag) : "memory");
    const int q = 8 * (2 * s + hw) + 2 * (tw & 3);
    const int na = 64 * hkv + 16 * (tw >> 5) + ((tw & 31) >> 2), nb = na + 8;
    __nv_bfloat16* op = out + (size_t)(b * kSq + q) * kD;
    op[na] = __float2bfloat16(y0); op[kD + na] = __float2bfloat16(y1);
    op[nb] = __float2bfloat16(y2); op[kD + nb] = __float2bfloat16(y3);
  }
  if (tid == 0) TS(6);
}

typedef CUresult (*EncodeFn)(CUtensorMap*, CUtensorMapDataType, cuuint32_t, void*, const cuuint64_t*, const cuuint64_t*,
                             const cuuint32_t*, const cuuint32_t*, CUtensorMapInterleave, CUtensorMapSwizzle,
                             CUtensorMapL2promotion, CUtensorMapFloatOOBfill);

}

extern "C" void kernel_launch(void* const* d_in, const int* in_sizes, int n_in, void* d_out, int out_size) {
  (void)in_sizes; (void)n_in; (void)out_size;
  static CUtensorMap tmK, tmV, tmX, tmWq, tmWo, tmV2;
  static const void* cached[5] = {nullptr, nullptr, nullptr, nullptr, nullptr};
  static EncodeFn enc = nullptr;
  if (!enc) {
    cudaDriverEntryPointQueryResult qr;
    cudaGetDriverEntryPoint("cuTensorMapEncodeTiled", (void**)&enc, cudaEnableDefault, &qr);
    cudaFuncSetAttribute(fused_attn_kernel, cudaFuncAttributeMaxDynamicSharedMemorySize, (int)kSmemBytes);
  }
  if (cached[0] != d_in[0] || cached[1] != d_in[1] || cached[2] != d_in[2] || cached[3] != d_in[3] || cached[4] != d_in[4]) {
    const cuuint32_t es[4] = {1, 1, 1, 1};
    {
      const cuuint64_t dims[3] = {64, (cuuint64_t)kB * kHkv * kSk, 4};
      const cuuint64_t strides[2] = {kDh * 2, 128};
      const cuuint32_t box[3] = {64, 64, 4};
      enc(&tmK, CU_TENSOR_MAP_DATA_TYPE_BFLOAT16, 3, d_in[1], dims, strides, box, es, CU_TENSOR_MAP_INTERLEAVE_NONE,
          CU_TENSOR_MAP_SWIZZLE_128B, CU_TENSOR_MAP_L2_PROMOTION_L2_256B, CU_TENSOR_MAP_FLOAT_OOB_FILL_NONE);
      enc(&tmV, CU_TENSOR_MAP_DATA_TYPE_BFLOAT16, 3, d_in[2], dims, strides, box, es, CU_TENSOR_MAP_INTERLEAVE_NONE,
          CU_TENSOR_MAP_SWIZZLE_128B, CU_TENSOR_MAP_L2_PROMOTION_L2_256B, CU_TENSOR_MAP_FLOAT_OOB_FILL_NONE);
    }
    {
      const cuuint64_t dims[3] = {64, (cuuint64_t)kB * kHkv * kSk, 4};
      const cuuint64_t strides[2] = {kDh * 2, 128};
      const cuuint32_t box[3] = {64, 128, 1};
      enc(&tmV2, CU_TENSOR_MAP_DATA_TYPE_BFLOAT16, 3, d_in[2], dims, strides, box, es, CU_TENSOR_MAP_INTERLEAVE_NONE,
          CU_TENSOR_MAP_SWIZZLE_128B, CU_TENSOR_MAP_L2_PROMOTION_L2_128B, CU_TENSOR_MAP_FLOAT_OOB_FILL_NONE);
    }
    {
      const cuuint64_t dims[3] = {64, (cuuint64_t)kB * kSq, 7};
      const cuuint64_t strides[2] = {kD * 2, 128};
      const cuuint32_t box[3] = {64, 32, 7};
      enc(&tmX, CU_TENSOR_MAP_DATA_TYPE_BFLOAT16, 3, d_in[0], dims, strides, box, es, CU_TENSOR_MAP_INTERLEAVE_NONE,
          CU_TENSOR_MAP_SWIZZLE_128B, CU_TENSOR_MAP_L2_PROMOTION_L2_128B, CU_TENSOR_MAP_FLOAT_OOB_FILL_NONE);
    }
    {
      const cuuint64_t dims[3] = {64, (cuuint64_t)kD, (cuuint64_t)kHq * kDh / 64};
      const cuuint64_t strides[2] = {(cuuint64_t)kHq * kDh * 2, 128};
      const cuuint32_t box[3] = {64, 64, 4};
      enc(&tmWq, CU_TENSOR_MAP_DATA_TYPE_BFLOAT16, 3, d_in[3], dims, strides, box, es, CU_TENSOR_MAP_INTERLEAVE_NONE,
          CU_TENSOR_MAP_SWIZZLE_128B, CU_TENSOR_MAP_L2_PROMOTION_L2_256B, CU_TENSOR_MAP_FLOAT_OOB_FILL_NONE);
    }
    {
      const cuuint64_t dims[4] = {(cuuint64_t)kD, 128, 2, (cuuint64_t)kHq};
      const cuuint64_t strides[3] = {kD * 2, (cuuint64_t)128 * kD * 2, (cuuint64_t)256 * kD * 2};
      const cuuint32_t box[4] = {64, 128, 1, 2};
      enc(&tmWo, CU_TENSOR_MAP_DATA_TYPE_BFLOAT16, 4, d_in[4], dims, strides, box, es, CU_TENSOR_MAP_INTERLEAVE_NONE,
          CU_TENSOR_MAP_SWIZZLE_128B, CU_TENSOR_MAP_L2_PROMOTION_L2_128B, CU_TENSOR_MAP_FLOAT_OOB_FILL_NONE);
    }
    for (int i = 0; i < 5; i++) cached[i] = d_in[i];
  }
  fused_attn_kernel<<<128, kThreads, kSmemBytes>>>(tmK, tmV, tmX, tmWq, tmWo, tmV2, (__nv_bfloat16*)d_out);
}
```
